```python
import torch

def _softmax(x, axis=-1):
    return torch.softmax(x, dim=axis)
def _gelu(x):
    return torch.nn.functional.gelu(x, approximate="tanh")
def _silu(x):
    return torch.nn.functional.silu(x)
def _sigmoid(x):
    return torch.sigmoid(x)
def _layernorm(x, axis=-1, eps=1e-5):
    m = x.mean(dim=axis, keepdim=True)
    v = x.var(dim=axis, keepdim=True, unbiased=False)
    return (x - m) / torch.sqrt(v + eps)
def _scatter_add(tgt, idx, src, axis=0):
    return tgt.clone().index_add_(axis, idx, src)
def _segment_sum(src, seg, n):
    out = torch.zeros((n,) + src.shape[1:], dtype=src.dtype)
    return out.index_add_(0, seg, src)
def _pad(x, pw):
    flat = tuple(v for pair in reversed(pw) for v in pair)
    return torch.nn.functional.pad(x, flat)

kernel_name = 'standalone__low_rank_proj_linformer__prompt'

def setup_inputs():

    _w = (lambda a: (lambda t: t.to(torch.bfloat16) if t.is_floating_point() else t)(torch.as_tensor(a)))
    B, H, Sq, Skv, Dh, R = 1, 32, 2048, 2048, 128, 8
    return {
        "q": _w((lambda *s: torch.randn(*s, dtype=torch.bfloat16) * 0.8)(B, H, Sq, Dh)),
        "k": _w((lambda *s: torch.randn(*s, dtype=torch.bfloat16) * 0.8)(B, H, Skv, Dh)),
        "v": _w((lambda *s: torch.randn(*s, dtype=torch.bfloat16) * 0.05)(B, H, Skv, Dh)),
        "e_proj": _w((lambda *s: torch.randn(*s, dtype=torch.bfloat16) * 0.8)(R, Skv) * (Skv ** -0.5)),
        "f_proj": _w((lambda *s: torch.randn(*s, dtype=torch.bfloat16) * 0.05)(R, Skv) * (Skv ** -0.5)),
    }

def reference(q, k, v, e_proj, f_proj):
    B, H, Sq, Dh = q.shape
    kp = torch.einsum("rn,bhnd->bhrd", e_proj, k)
    vp = torch.einsum("rn,bhnd->bhrd", f_proj, v)
    scores = torch.einsum("bhqd,bhrd->bhqr", q, kp) * (Dh ** -0.5)
    p = _softmax(scores, axis=-1)
    o = torch.einsum("bhqr,bhrd->bhqd", p, vp)
    return o
```

```cpp
#include <cuda_runtime.h>
#include <cuda_bf16.h>
#include <cuda.h>
#include <stdint.h>

namespace lf {
__device__ __forceinline__ uint32_t smem_u32(const void* p) { return (uint32_t)__cvta_generic_to_shared(p); }
__device__ __forceinline__ void mbar_init(uint32_t bar, uint32_t cnt) { asm volatile("mbarrier.init.shared::cta.b64 [%0], %1;" :: "r"(bar), "r"(cnt) : "memory"); }
__device__ __forceinline__ void mbar_expect_tx(uint32_t bar, uint32_t bytes) { asm volatile("mbarrier.arrive.expect_tx.shared::cta.b64 _, [%0], %1;" :: "r"(bar), "r"(bytes) : "memory"); }
__device__ __forceinline__ void mbar_arrive(uint32_t bar) { asm volatile("mbarrier.arrive.shared::cta.b64 _, [%0];" :: "r"(bar) : "memory"); }
__device__ __forceinline__ bool mbar_try(uint32_t bar, uint32_t parity) {
    uint32_t ok;
    asm volatile("{\n.reg .pred p;\nmbarrier.try_wait.parity.shared::cta.b64 p, [%1], %2;\nselp.u32 %0, 1, 0, p;\n}" : "=r"(ok) : "r"(bar), "r"(parity) : "memory");
    return ok;
}
__device__ __forceinline__ bool mbar_test(uint32_t bar, uint32_t parity) {
    uint32_t ok;
    asm volatile("{\n.reg .pred p;\nmbarrier.test_wait.parity.shared::cta.b64 p, [%1], %2;\nselp.u32 %0, 1, 0, p;\n}" : "=r"(ok) : "r"(bar), "r"(parity) : "memory");
    return ok;
}
__device__ __forceinline__ bool mbar_try_cl(uint32_t bar, uint32_t parity) {
    uint32_t ok;
    asm volatile("{\n.reg .pred p;\nmbarrier.try_wait.parity.relaxed.cluster.shared::cta.b64 p, [%1], %2;\nselp.u32 %0, 1, 0, p;\n}" : "=r"(ok) : "r"(bar), "r"(parity) : "memory");
    return ok;
}
__device__ __forceinline__ void mbar_wait(uint32_t bar, uint32_t parity) {
    int n = 0;
    while (!mbar_try(bar, parity)) { if (++n > (1 << 20)) __trap(); }
}
__device__ __forceinline__ void mbar_wait_cl(uint32_t bar, uint32_t parity) {
    int n = 0;
    while (!mbar_try_cl(bar, parity)) { if (++n > (1 << 20)) __trap(); }
    asm volatile("fence.acquire.sync_restrict::shared::cluster.cluster;" ::: "memory");
}
__device__ __forceinline__ void tma3(uint32_t dst, const CUtensorMap* m, int c1, int c2, uint32_t bar, uint64_t pol) {
    asm volatile("cp.async.bulk.tensor.3d.shared::cluster.global.mbarrier::complete_tx::bytes.L2::cache_hint [%0], [%1, {%3, %4, %5}], [%2], %6;"
        :: "r"(dst), "l"(m), "r"(bar), "r"(0), "r"(c1), "r"(c2), "l"(pol) : "memory");
}
__device__ __forceinline__ void tma3n(uint32_t dst, const CUtensorMap* m, int c1, int c2, uint32_t bar) {
    asm volatile("cp.async.bulk.tensor.3d.shared::cluster.global.mbarrier::complete_tx::bytes [%0], [%1, {%3, %4, %5}], [%2];"
        :: "r"(dst), "l"(m), "r"(bar), "r"(0), "r"(c1), "r"(c2) : "memory");
}
__device__ __forceinline__ void ldsm4(uint32_t a, uint32_t& r0, uint32_t& r1, uint32_t& r2, uint32_t& r3) {
    asm volatile("ldmatrix.sync.aligned.m8n8.x4.shared.b16 {%0,%1,%2,%3}, [%4];" : "=r"(r0), "=r"(r1), "=r"(r2), "=r"(r3) : "r"(a) : "memory");
}
__device__ __forceinline__ void ldsm4t(uint32_t a, uint32_t& r0, uint32_t& r1, uint32_t& r2, uint32_t& r3) {
    asm volatile("ldmatrix.sync.aligned.m8n8.x4.trans.shared.b16 {%0,%1,%2,%3}, [%4];" : "=r"(r0), "=r"(r1), "=r"(r2), "=r"(r3) : "r"(a) : "memory");
}
__device__ __forceinline__ void mma16816(float* c, uint32_t a0, uint32_t a1, uint32_t a2, uint32_t a3, uint32_t b0, uint32_t b1) {
    asm volatile("mma.sync.aligned.m16n8k16.row.col.f32.bf16.bf16.f32 {%0,%1,%2,%3}, {%4,%5,%6,%7}, {%8,%9}, {%0,%1,%2,%3};"
        : "+f"(c[0]), "+f"(c[1]), "+f"(c[2]), "+f"(c[3]) : "r"(a0), "r"(a1), "r"(a2), "r"(a3), "r"(b0), "r"(b1));
}
__device__ __forceinline__ void mma1688z(float* d, uint32_t a0, uint32_t a1, uint32_t b0) {
    asm volatile("mma.sync.aligned.m16n8k8.row.col.f32.bf16.bf16.f32 {%0,%1,%2,%3}, {%4,%5}, {%6}, {%7,%7,%7,%7};"
        : "=f"(d[0]), "=f"(d[1]), "=f"(d[2]), "=f"(d[3]) : "r"(a0), "r"(a1), "r"(b0), "f"(0.f));
}
__device__ __forceinline__ uint32_t pack_bf16(float lo, float hi) { uint32_t r; asm("cvt.rn.bf16x2.f32 %0, %1, %2;" : "=r"(r) : "f"(hi), "f"(lo)); return r; }
__device__ __forceinline__ float bf_lo(uint32_t x) { return __uint_as_float(x << 16); }
__device__ __forceinline__ float bf_hi(uint32_t x) { return __uint_as_float(x & 0xffff0000u); }
__device__ __forceinline__ uint32_t mapa(uint32_t a, uint32_t r) { uint32_t d; asm("mapa.shared::cluster.u32 %0, %1, %2;" : "=r"(d) : "r"(a), "r"(r)); return d; }
__device__ __forceinline__ float ex2(float x) { float y; asm("ex2.approx.ftz.f32 %0, %1;" : "=f"(y) : "f"(x)); return y; }
__device__ __forceinline__ float rcp(float x) { float y; asm("rcp.approx.ftz.f32 %0, %1;" : "=f"(y) : "f"(x)); return y; }
__device__ __forceinline__ bool elect() {
    uint32_t p;
    asm volatile("{\n.reg .pred p;\nelect.sync _|p, 0xffffffff;\nselp.u32 %0, 1, 0, p;\n}" : "=r"(p));
    return p;
}
__device__ __forceinline__ void st_async4(uint32_t dst, uint32_t a, uint32_t b, uint32_t c, uint32_t d, uint32_t bar) {
    asm volatile("st.async.weak.shared::cluster.mbarrier::complete_tx::bytes.v4.b32 [%0], {%1,%2,%3,%4}, [%5];" :: "r"(dst), "r"(a), "r"(b), "r"(c), "r"(d), "r"(bar) : "memory");
}
__device__ __forceinline__ uint4 lds128(uint32_t a) { uint4 v; asm volatile("ld.shared.v4.b32 {%0,%1,%2,%3}, [%4];" : "=r"(v.x), "=r"(v.y), "=r"(v.z), "=r"(v.w) : "r"(a) : "memory"); return v; }
__device__ __forceinline__ uint32_t lds32(uint32_t a) { uint32_t v; asm volatile("ld.shared.b32 %0, [%1];" : "=r"(v) : "r"(a) : "memory"); return v; }
__device__ __forceinline__ uint64_t gtime() { uint64_t t; asm volatile("mov.u64 %0, %%globaltimer;" : "=l"(t)); return t; }
#define CLUSTER_ARRIVE() asm volatile("fence.mbarrier_init.release.cluster;\nbarrier.cluster.arrive.relaxed.aligned;" ::: "memory")
#define CLUSTER_WAIT() asm volatile("barrier.cluster.wait.aligned;" ::: "memory")
__device__ __forceinline__ uint32_t softmax8(float s0, float s1) {
    const float scale = 0.08838834764831845f, l2e = 1.4426950408889634f;
    uint32_t r = pack_bf16(s0, s1);
    r = pack_bf16(bf_lo(r) * scale, bf_hi(r) * scale);
    float x0 = bf_lo(r), x1 = bf_hi(r);
    float m = fmaxf(x0, x1);
    m = fmaxf(m, __shfl_xor_sync(0xffffffffu, m, 1));
    m = fmaxf(m, __shfl_xor_sync(0xffffffffu, m, 2));
    x0 = ex2((x0 - m) * l2e); x1 = ex2((x1 - m) * l2e);
    float s = x0 + x1;
    s += __shfl_xor_sync(0xffffffffu, s, 1);
    s += __shfl_xor_sync(0xffffffffu, s, 2);
    s = rcp(s);
    return pack_bf16(x0 * s, x1 * s);
}
}

namespace lf {
constexpr int CL = 8, HPC = 4;
constexpr int KVB = 16384, QB = 8192;
constexpr int FINB = 2048 + 4 * 576;
constexpr int NTHREADS = 14 * 32;
constexpr int O_KV = 0, O_Q = 8 * KVB, O_E = O_Q + 8 * QB, O_FIN = O_E + 8192, O_IN = O_FIN + HPC * FINB, O_BAR = O_IN + 4096;
constexpr int SMEM = O_BAR + 8 * 41;
struct Params { CUtensorMap mk, mv, mq, me, mf; uint32_t tab[8][32]; };

__global__ void __cluster_dims__(CL, 1, 1) __launch_bounds__(NTHREADS, 1)
lf_kernel(const __grid_constant__ Params P, __nv_bfloat16* __restrict__ O, int ROFF) {
    constexpr int W0 = 2;
    extern __shared__ __align__(1024) unsigned char smem_raw[];
    const uint32_t sb = smem_u32(smem_raw);
    const uint32_t s_kv = sb + O_KV, s_q = sb + O_Q, s_e = sb + O_E, s_fin = sb + O_FIN, s_in = sb + O_IN;
    const uint32_t b_kvf = sb + O_BAR, b_kve = b_kvf + 64, b_qf = b_kve + 64, b_qe = b_qf + 64, b_in = b_qe + 64, b_fin = b_in + 32, b_e = b_fin + 32;
    const int warp = __shfl_sync(0xffffffffu, threadIdx.x >> 5, 0), lane = threadIdx.x & 31;
    const int rank = blockIdx.x & (CL - 1), cid = blockIdx.x >> 3;
    const int isV = rank >> 2, part = rank & 3;
    const int kvrow = cid * 2048 + part * 512, qrow = cid * 2048 + rank * 256;
    uint64_t pol; asm volatile("createpolicy.fractional.L2::evict_first.b64 %0, 1.0;" : "=l"(pol));
    const CUtensorMap* mkv = isV ? &P.mv : &P.mk;
    const bool leader = elect();
    const uint32_t tbase = (uint32_t)gtime() + rank * ROFF;
    uint32_t tabv = 0;
    if (leader) {
        if (warp == 13) {
#pragma unroll 1
            for (int k = 0; k < W0; k++) {
                mbar_init(b_kvf + 8 * k, 1);
                asm volatile("fence.mbarrier_init.release.cluster;" ::: "memory");
                mbar_expect_tx(b_kvf + 8 * k, KVB); tma3(s_kv + k * KVB, mkv, kvrow + k * 64, 0, b_kvf + 8 * k, pol);
            }
        } else if (warp < 8) {
            if (warp >= W0) mbar_init(b_kvf + 8 * warp, 1);
            mbar_init(b_kve + 8 * warp, 4);
            mbar_init(b_qf + 8 * warp, 1);
            mbar_init(b_qe + 8 * warp, 1);
            mbar_init(b_in + 8 * warp, 1);
            mbar_expect_tx(b_in + 8 * warp, 4096);
        } else if (warp == 8) {
            mbar_init(b_e, 1);
            asm volatile("fence.mbarrier_init.release.cluster;" ::: "memory");
            mbar_expect_tx(b_e, 8192);
            tma3n(s_e, isV ? &P.mf : &P.me, 0, part * 8, b_e);
        }
    }
    __syncwarp();
    if (warp == 13) tabv = P.tab[cid][lane];
    CLUSTER_ARRIVE();
    CLUSTER_WAIT();

    if (warp == 13) {
        int b = 0, k = W0;
#pragma unroll 1
        for (int i = W0; i < 64; i++) {
            uint32_t e = __shfl_sync(0xffffffffu, tabv, i >> 1);
            e = (i & 1) ? (e >> 16) : (e & 0xffff);
            const uint32_t tt = tbase + (e & 0x7fff);
            const bool isq = e >> 15;
            const int n = isq ? b : k, s = n & 7;
            const uint32_t bf = (isq ? b_qf : b_kvf) + 8 * s;
            if (n >= 8) mbar_wait(bf + 64, ((n >> 3) & 1) ^ 1);
            if (leader) mbar_expect_tx(bf, isq ? QB : KVB);
            const uint32_t dst = isq ? s_q + s * QB : s_kv + s * KVB;
            const int row = (isq ? qrow + s * 32 : kvrow + s * 64) + (n >> 3) * (8 * 2048);
            const CUtensorMap* mp = isq ? &P.mq : mkv;
            while ((int)((uint32_t)gtime() - tt) < 0) { }
            if (leader) tma3(dst, mp, row, 0, bf, pol);
            if (isq) b++; else k++;
        }
    } else if (warp >= 8 && warp < 12) {
        const int w = warp - 8;
        const uint32_t l7 = lane & 7;
        const uint32_t cA = (w & 1) * 4 + ((lane >> 3) & 1);
        const uint32_t a_base = s_kv + (w >> 1) * 8192 + (l7 + 8 * (lane >> 4)) * 128;
        const uint32_t a0 = a_base + ((cA ^ l7) << 4), a1 = a_base + (((cA + 2) ^ l7) << 4);
        const uint32_t e0 = s_e + l7 * 128 + (((lane >> 3) ^ l7) << 4), e1 = s_e + l7 * 128 + ((((lane >> 3) + 4) ^ l7) << 4);
        const uint32_t dst = mapa(s_in + part * 1024 + lane * 16, isV * 4 + w), rb = mapa(b_in, isV * 4 + w);
        mbar_wait(b_e, 0);
#pragma unroll 1
        for (int j = 0; j < HPC; j++) {
            float c0[4] = {0, 0, 0, 0}, c1[4] = {0, 0, 0, 0}, c2[4] = {0, 0, 0, 0}, c3[4] = {0, 0, 0, 0};
#pragma unroll 1
            for (int c = 0; c < 8; c++) {
                uint32_t e[8], a[32];
                ldsm4(e0 + c * 1024, e[0], e[1], e[2], e[3]);
                ldsm4(e1 + c * 1024, e[4], e[5], e[6], e[7]);
                mbar_wait(b_kvf + 8 * c, j & 1);
#pragma unroll
                for (int s = 0; s < 4; s++) {
                    ldsm4t(a0 + c * KVB + s * 2048, a[8 * s], a[8 * s + 1], a[8 * s + 2], a[8 * s + 3]);
                    ldsm4t(a1 + c * KVB + s * 2048, a[8 * s + 4], a[8 * s + 5], a[8 * s + 6], a[8 * s + 7]);
                }
#pragma unroll
                for (int s = 0; s < 4; s++) {
                    mma16816((s & 1) ? c2 : c0, a[8 * s], a[8 * s + 1], a[8 * s + 2], a[8 * s + 3], e[2 * s], e[2 * s + 1]);
                    mma16816((s & 1) ? c3 : c1, a[8 * s + 4], a[8 * s + 5], a[8 * s + 6], a[8 * s + 7], e[2 * s], e[2 * s + 1]);
                }
                __syncwarp();
                if (leader) mbar_arrive(b_kve + 8 * c);
            }
            if (j > 0) mbar_wait_cl(b_fin + 8 * (j - 1), 0);
            st_async4(dst, __float_as_uint(c0[0] + c2[0]), __float_as_uint(c0[1] + c2[1]), __float_as_uint(c0[2] + c2[2]), __float_as_uint(c0[3] + c2[3]), rb + 8 * j);
            st_async4(dst + 512, __float_as_uint(c1[0] + c3[0]), __float_as_uint(c1[1] + c3[1]), __float_as_uint(c1[2] + c3[2]), __float_as_uint(c1[3] + c3[3]), rb + 8 * j);
        }
    } else if (warp == 12) {
        const uint32_t foff = s_fin + (isV ? 2048 + part * 576 : part * 512) + lane * 16;
#pragma unroll 1
        for (int j = 0; j < HPC; j++) {
            mbar_wait_cl(b_in + 8 * j, 0);
            uint4 x[8];
#pragma unroll
            for (int s = 0; s < 8; s++) x[s] = lds128(s_in + s * 512 + lane * 16);
            uint32_t wv[4];
#pragma unroll
            for (int i = 0; i < 2; i++) {
#define F_(v) __uint_as_float(v)
                float s0 = (F_(x[i].x) + F_(x[2 + i].x)) + (F_(x[4 + i].x) + F_(x[6 + i].x));
                float s1 = (F_(x[i].y) + F_(x[2 + i].y)) + (F_(x[4 + i].y) + F_(x[6 + i].y));
                float s2 = (F_(x[i].z) + F_(x[2 + i].z)) + (F_(x[4 + i].z) + F_(x[6 + i].z));
                float s3 = (F_(x[i].w) + F_(x[2 + i].w)) + (F_(x[4 + i].w) + F_(x[6 + i].w));
                wv[2 * i] = pack_bf16(s0, s1); wv[2 * i + 1] = pack_bf16(s2, s3);
            }
            if (!isV) {
#pragma unroll
                for (int i = 0; i < 4; i++) asm volatile("movmatrix.sync.aligned.m8n8.trans.b16 %0, %0;" : "+r"(wv[i]));
            }
#pragma unroll
            for (int r = 0; r < CL; r++) st_async4(mapa(foff + j * FINB, r), wv[0], wv[1], wv[2], wv[3], mapa(b_fin + 8 * j, r));
        }
    } else {
        const int g = lane >> 2, t = lane & 3;
        const uint32_t qx = lane & 7, qc = lane >> 4;
        const uint32_t qb = s_q + warp * QB + (qx + 8 * ((lane >> 3) & 1)) * 128;
        const uint32_t voff = 2048 + (g >> 2) * 576 + t * 16 + (g & 3) * 4;
        unsigned char* op = reinterpret_cast<unsigned char*>(O) + ((size_t)(qrow + warp * 32 + 2 * t)) * 256 + g * 16;
#pragma unroll 1
        for (int j = 0; j < HPC; j++) {
            const uint32_t fin = s_fin + j * FINB;
            mbar_wait(b_qf + 8 * warp, j & 1);
            uint32_t a[64];
#pragma unroll
            for (int m = 0; m < 2; m++)
#pragma unroll
                for (int u = 0; u < 8; u++)
                    ldsm4(qb + m * 2048 + (u >> 2) * 4096 + (((2 * (u & 3) + qc) ^ qx) << 4), a[32 * m + 4 * u], a[32 * m + 4 * u + 1], a[32 * m + 4 * u + 2], a[32 * m + 4 * u + 3]);
            __syncwarp();
            if (leader) mbar_arrive(b_qe + 8 * warp);
            mbar_wait_cl(b_fin + 8 * j, 0);
            float sc[4][4];
#pragma unroll
            for (int i = 0; i < 4; i++) { sc[i][0] = sc[i][1] = sc[i][2] = sc[i][3] = 0.f; }
#pragma unroll
            for (int u = 0; u < 4; u++) {
                const uint4 kf = lds128(fin + u * 512 + lane * 16);
#pragma unroll
                for (int m = 0; m < 2; m++) {
                    mma16816(sc[2 * m], a[32 * m + 8 * u], a[32 * m + 8 * u + 1], a[32 * m + 8 * u + 2], a[32 * m + 8 * u + 3], kf.x, kf.y);
                    mma16816(sc[2 * m + 1], a[32 * m + 8 * u + 4], a[32 * m + 8 * u + 5], a[32 * m + 8 * u + 6], a[32 * m + 8 * u + 7], kf.z, kf.w);
                }
            }
            uint32_t vw[16];
#pragma unroll
            for (int x = 0; x < 16; x++) vw[x] = lds32(fin + voff + (x >> 3) * (2 * 576) + (x & 7) * 64);
            uint32_t p[4];
#pragma unroll
            for (int m = 0; m < 2; m++) {
                p[2 * m] = softmax8(sc[2 * m][0] + sc[2 * m + 1][0], sc[2 * m][1] + sc[2 * m + 1][1]);
                p[2 * m + 1] = softmax8(sc[2 * m][2] + sc[2 * m + 1][2], sc[2 * m][3] + sc[2 * m + 1][3]);
            }
#pragma unroll
            for (int u = 0; u < 4; u++) {
#pragma unroll
                for (int H = 0; H < 2; H++) {
                    uint32_t r0[4], r1[4];
#pragma unroll
                    for (int jj = 0; jj < 4; jj++) {
                        float d[4];
                        mma1688z(d, vw[8 * H + 2 * jj], vw[8 * H + 2 * jj + 1], p[u]);
                        r0[jj] = pack_bf16(d[0], d[2]); r1[jj] = pack_bf16(d[1], d[3]);
                    }
                    *reinterpret_cast<uint4*>(op + u * 2048 + H * 128) = make_uint4(r0[0], r0[1], r0[2], r0[3]);
                    *reinterpret_cast<uint4*>(op + u * 2048 + H * 128 + 256) = make_uint4(r1[0], r1[1], r1[2], r1[3]);
                }
            }
            op += (size_t)8 * 2048 * 256;
        }
    }
}
}

typedef CUresult (*EncodeFn)(CUtensorMap*, CUtensorMapDataType, cuuint32_t, void*, const cuuint64_t*, const cuuint64_t*, const cuuint32_t*, const cuuint32_t*, CUtensorMapInterleave, CUtensorMapSwizzle, CUtensorMapL2promotion, CUtensorMapFloatOOBfill);

static void encode3(EncodeFn enc, CUtensorMap* m, const void* p, cuuint64_t d1, cuuint64_t d2, cuuint64_t s1, cuuint32_t b1, cuuint32_t b2) {
    cuuint64_t dims[3] = {64, d1, d2}; cuuint64_t str[2] = {s1, 128}; cuuint32_t box[3] = {64, b1, b2}; cuuint32_t es[3] = {1, 1, 1};
    enc(m, CU_TENSOR_MAP_DATA_TYPE_BFLOAT16, 3, (void*)p, dims, str, box, es, CU_TENSOR_MAP_INTERLEAVE_NONE, CU_TENSOR_MAP_SWIZZLE_128B,
        CU_TENSOR_MAP_L2_PROMOTION_NONE, CU_TENSOR_MAP_FLOAT_OOB_FILL_NONE);
}

extern "C" void kernel_launch(void* const* d_in, const int* in_sizes, int n_in, void* d_out, int out_size) {
    static EncodeFn enc = nullptr;
    if (!enc) {
        cudaDriverEntryPointQueryResult qr;
        cudaGetDriverEntryPoint("cuTensorMapEncodeTiled", (void**)&enc, cudaEnableDefault, &qr);
        cudaFuncSetAttribute(lf::lf_kernel, cudaFuncAttributeMaxDynamicSharedMemorySize, lf::SMEM);
    }
    lf::Params P;
    encode3(enc, &P.mq, d_in[0], 65536, 2, 256, 32, 2);
    encode3(enc, &P.mk, d_in[1], 65536, 2, 256, 64, 2);
    encode3(enc, &P.mv, d_in[2], 65536, 2, 256, 64, 2);
    encode3(enc, &P.me, d_in[3], 8, 32, 4096, 8, 8);
    encode3(enc, &P.mf, d_in[4], 8, 32, 4096, 8, 8);
    for (int c = 0; c < 8; c++) {
        int kv[32], q[32], nq = 0, t = 600 - 3 * 325;
        for (int k = 0; k < 32; k++) {
            kv[k] = t < 0 ? 0 : t;
            if (k >= 8) { q[nq++] = t + 300; t += 490; } else t += 325;
        }
        while (nq < 32) { q[nq++] = t; t += 220; }
        unsigned short ent[64]; int k = 0, b = 0;
        for (int x = 0; x < 64; x++) {
            bool tq = (k == 32) || (b < 32 && q[b] < kv[k]);
            if (tq) ent[x] = (unsigned short)(0x8000 | q[b++]); else ent[x] = (unsigned short)kv[k++];
        }
        for (int x = 0; x < 32; x++) P.tab[c][x] = ent[2 * x] | ((uint32_t)ent[2 * x + 1] << 16);
    }
    lf::lf_kernel<<<64, lf::NTHREADS, lf::SMEM, cudaStreamPerThread>>>(P, (__nv_bfloat16*)d_out, 0);
}
```

```cpp
#include <cuda_runtime.h>
#include <cuda_bf16.h>
#include <cuda.h>
#include <stdint.h>

namespace lf {

__device__ __forceinline__ uint32_t smem_u32(const void* p) { return (uint32_t)__cvta_generic_to_shared(p); }
__device__ __forceinline__ void mbar_init(uint32_t bar, uint32_t cnt) {
    asm volatile("mbarrier.init.shared::cta.b64 [%0], %1;" :: "r"(bar), "r"(cnt) : "memory");
}
__device__ __forceinline__ void mbar_expect_tx(uint32_t bar, uint32_t bytes) {
    asm volatile("mbarrier.arrive.expect_tx.shared::cta.b64 _, [%0], %1;" :: "r"(bar), "r"(bytes) : "memory");
}
__device__ __forceinline__ void mbar_arrive(uint32_t bar) {
    asm volatile("mbarrier.arrive.shared::cta.b64 _, [%0];" :: "r"(bar) : "memory");
}
__device__ __forceinline__ bool mbar_try(uint32_t bar, uint32_t parity) {
    uint32_t ok;
    asm volatile("{\n.reg .pred p;\nmbarrier.try_wait.parity.shared::cta.b64 p, [%1], %2;\nselp.u32 %0, 1, 0, p;\n}"
                 : "=r"(ok) : "r"(bar), "r"(parity) : "memory");
    return ok;
}
__device__ __forceinline__ bool mbar_try_cl(uint32_t bar, uint32_t parity) {
    uint32_t ok;
    asm volatile("{\n.reg .pred p;\nmbarrier.try_wait.parity.relaxed.cluster.shared::cta.b64 p, [%1], %2;\nselp.u32 %0, 1, 0, p;\n}"
                 : "=r"(ok) : "r"(bar), "r"(parity) : "memory");
    return ok;
}
__device__ __forceinline__ bool mbar_test_cl(uint32_t bar, uint32_t parity) {
    uint32_t ok;
    asm volatile("{\n.reg .pred p;\nmbarrier.test_wait.parity.relaxed.cluster.shared::cta.b64 p, [%1], %2;\nselp.u32 %0, 1, 0, p;\n}"
                 : "=r"(ok) : "r"(bar), "r"(parity) : "memory");
    return ok;
}
__device__ __forceinline__ void acquire_cl() { asm volatile("fence.acquire.sync_restrict::shared::cluster.cluster;" ::: "memory"); }
__device__ __forceinline__ void mbar_wait(uint32_t bar, uint32_t parity) {
    int n = 0;
    while (!mbar_try(bar, parity)) { if (++n > (1 << 20)) __trap(); }
}
__device__ __forceinline__ void mbar_wait_cl(uint32_t bar, uint32_t parity) {
    int n = 0;
    while (!mbar_try_cl(bar, parity)) { if (++n > (1 << 20)) __trap(); }
    acquire_cl();
}
__device__ __forceinline__ uint32_t now_ns() { uint32_t t; asm volatile("mov.u32 %0, %%globaltimer_lo;" : "=r"(t)); return t; }
__device__ __forceinline__ void wait_until(uint32_t t) {
    for (int n = 0; (int)(now_ns() - t) < 0 && n < 4096; n++) { }
}
__device__ __forceinline__ void tma_load(uint32_t dst, const CUtensorMap* m, int row, uint32_t bar, uint64_t pol) {
    asm volatile("cp.async.bulk.tensor.3d.shared::cluster.global.mbarrier::complete_tx::bytes.L2::cache_hint [%0], [%1, {%3, %4, %3}], [%2], %5;"
                 :: "r"(dst), "l"(m), "r"(bar), "r"(0), "r"(row), "l"(pol) : "memory");
}
__device__ __forceinline__ void ldsm4(uint32_t a, uint32_t* r) {
    asm volatile("ldmatrix.sync.aligned.m8n8.x4.shared.b16 {%0,%1,%2,%3}, [%4];" : "=r"(r[0]), "=r"(r[1]), "=r"(r[2]), "=r"(r[3]) : "r"(a) : "memory");
}
__device__ __forceinline__ void ldsm4t(uint32_t a, uint32_t* r) {
    asm volatile("ldmatrix.sync.aligned.m8n8.x4.trans.shared.b16 {%0,%1,%2,%3}, [%4];" : "=r"(r[0]), "=r"(r[1]), "=r"(r[2]), "=r"(r[3]) : "r"(a) : "memory");
}
__device__ __forceinline__ void mma16816(float* c, const uint32_t* a, uint32_t b0, uint32_t b1) {
    asm volatile("mma.sync.aligned.m16n8k16.row.col.f32.bf16.bf16.f32 {%0,%1,%2,%3}, {%4,%5,%6,%7}, {%8,%9}, {%0,%1,%2,%3};"
                 : "+f"(c[0]), "+f"(c[1]), "+f"(c[2]), "+f"(c[3]) : "r"(a[0]), "r"(a[1]), "r"(a[2]), "r"(a[3]), "r"(b0), "r"(b1));
}
__device__ __forceinline__ void mma1688z(float* d, uint32_t a0, uint32_t a1, uint32_t b0) {
    asm volatile("mma.sync.aligned.m16n8k8.row.col.f32.bf16.bf16.f32 {%0,%1,%2,%3}, {%4,%5}, {%6}, {%7,%7,%7,%7};"
                 : "=f"(d[0]), "=f"(d[1]), "=f"(d[2]), "=f"(d[3]) : "r"(a0), "r"(a1), "r"(b0), "f"(0.f));
}
__device__ __forceinline__ uint32_t pack_bf16(float lo, float hi) { uint32_t r; asm("cvt.rn.bf16x2.f32 %0, %1, %2;" : "=r"(r) : "f"(hi), "f"(lo)); return r; }
__device__ __forceinline__ float bf_lo(uint32_t x) { return __uint_as_float(x << 16); }
__device__ __forceinline__ float bf_hi(uint32_t x) { return __uint_as_float(x & 0xffff0000u); }
__device__ __forceinline__ uint32_t bfmax2(uint32_t a, uint32_t b) { uint32_t d; asm("max.bf16x2 %0, %1, %2;" : "=r"(d) : "r"(a), "r"(b)); return d; }
__device__ __forceinline__ float ex2(float x) { float y; asm("ex2.approx.ftz.f32 %0, %1;" : "=f"(y) : "f"(x)); return y; }
__device__ __forceinline__ float rcp(float x) { float y; asm("rcp.approx.ftz.f32 %0, %1;" : "=f"(y) : "f"(x)); return y; }
__device__ __forceinline__ uint32_t mapa(uint32_t a, uint32_t r) { uint32_t d; asm("mapa.shared::cluster.u32 %0, %1, %2;" : "=r"(d) : "r"(a), "r"(r)); return d; }
__device__ __forceinline__ bool elect() {
    uint32_t p;
    asm volatile("{\n.reg .pred p;\nelect.sync _|p, 0xffffffff;\nselp.u32 %0, 1, 0, p;\n}" : "=r"(p));
    return p;
}
__device__ __forceinline__ void st_async4(uint32_t dst, uint32_t a, uint32_t b, uint32_t c, uint32_t d, uint32_t bar) {
    asm volatile("st.async.weak.shared::cluster.mbarrier::complete_tx::bytes.v4.b32 [%0], {%1,%2,%3,%4}, [%5];"
                 :: "r"(dst), "r"(a), "r"(b), "r"(c), "r"(d), "r"(bar) : "memory");
}
__device__ __forceinline__ uint4 lds128(uint32_t a) {
    uint4 v; asm volatile("ld.shared.v4.b32 {%0,%1,%2,%3}, [%4];" : "=r"(v.x), "=r"(v.y), "=r"(v.z), "=r"(v.w) : "r"(a) : "memory"); return v;
}
__device__ __forceinline__ uint32_t lds32(uint32_t a) { uint32_t v; asm volatile("ld.shared.b32 %0, [%1];" : "=r"(v) : "r"(a) : "memory"); return v; }
__device__ __forceinline__ void sts128(uint32_t p, const uint32_t* r) {
    asm volatile("st.shared.v4.b32 [%0], {%1,%2,%3,%4};" :: "r"(p), "r"(r[0]), "r"(r[1]), "r"(r[2]), "r"(r[3]) : "memory");
}
__device__ __forceinline__ void cluster_arrive() {
    asm volatile("fence.mbarrier_init.release.cluster;\nbarrier.cluster.arrive.relaxed.aligned;" ::: "memory");
}
__device__ __forceinline__ void cluster_wait() { asm volatile("barrier.cluster.wait.aligned;" ::: "memory"); }

__device__ __forceinline__ void softmax8x2(float s0, float s1, float s2, float s3, uint32_t& pa, uint32_t& pb) {
    const float scale = 0.08838834764831845f, l2e = 1.4426950408889634f;
    uint32_t r0 = pack_bf16(s0, s2), r1 = pack_bf16(s1, s3);
    r0 = pack_bf16(bf_lo(r0) * scale, bf_hi(r0) * scale);
    r1 = pack_bf16(bf_lo(r1) * scale, bf_hi(r1) * scale);
    uint32_t m = bfmax2(r0, r1);
    const uint32_t m1 = __shfl_xor_sync(0xffffffffu, m, 1), m2 = __shfl_xor_sync(0xffffffffu, m, 2), m3 = __shfl_xor_sync(0xffffffffu, m, 3);
    m = bfmax2(bfmax2(m, m1), bfmax2(m2, m3));
    const float ma = bf_lo(m), mb = bf_hi(m);
    const float a0 = ex2((bf_lo(r0) - ma) * l2e), a1 = ex2((bf_lo(r1) - ma) * l2e);
    const float b0 = ex2((bf_hi(r0) - mb) * l2e), b1 = ex2((bf_hi(r1) - mb) * l2e);
    float sa = a0 + a1, sb = b0 + b1;
    const float sa1 = __shfl_xor_sync(0xffffffffu, sa, 1), sa2 = __shfl_xor_sync(0xffffffffu, sa, 2), sa3 = __shfl_xor_sync(0xffffffffu, sa, 3);
    const float sb1 = __shfl_xor_sync(0xffffffffu, sb, 1), sb2 = __shfl_xor_sync(0xffffffffu, sb, 2), sb3 = __shfl_xor_sync(0xffffffffu, sb, 3);
    sa = rcp((sa + sa1) + (sa2 + sa3));
    sb = rcp((sb + sb1) + (sb2 + sb3));
    pa = pack_bf16(a0 * sa, a1 * sa);
    pb = pack_bf16(b0 * sb, b1 * sb);
}

constexpr int CL = 8;
constexpr int HPC = 4;
constexpr int HSTR = 8 * 2048;
constexpr int KVB = 16384;
constexpr int QB = 8192;
constexpr int FINB = 2048 + 4 * 576;
constexpr int NPF = 3;
constexpr int W_KV = 16, W_RED = 20, W_PKV = 21, W_PQ = 22, NTHREADS = 23 * 32;
constexpr int O_KV = 0, O_Q = 8 * KVB, O_E = O_Q + 8 * QB, O_FIN = O_E + 8192, O_IN = O_FIN + HPC * FINB, O_BAR = O_IN + 4096;
constexpr int SMEM = O_BAR + 8 * 101;

struct Params { CUtensorMap mk, mv, mq, mo, me, mf; };

__device__ __forceinline__ int hinge(int x, int k) { return max(x - k, 0); }
__device__ __forceinline__ int kv_time(int k, int isV) {
    int t = -475 + 325 * k + 45 * hinge(k, 5) + 92 * hinge(k, 8);
    t += isV ? 168 * hinge(k, 24) - 267 * hinge(k, 28) : -84 * hinge(k, 24) + 42 * hinge(k, 28);
    return t;
}
__device__ __forceinline__ int q_time(int b, int isV) {
    return (isV ? 2487 : 2553) + 416 * b + 205 * hinge(b, 8) + 33 * hinge(b, 16) - 306 * hinge(b, 19) - 205 * hinge(b, 21)
           + 61 * hinge(b, 24) - 37 * hinge(b, 28);
}

#define DEV_START()
#define DEV_TIME(t)
#define DEV_END()

__global__ void __cluster_dims__(CL, 1, 1) __launch_bounds__(NTHREADS, 1)
lf_kernel(const unsigned char* __restrict__ Kp, const unsigned char* __restrict__ Vp, const __grid_constant__ Params P) {
    const uint32_t tbase = now_ns();
    uint64_t pol;
    asm volatile("createpolicy.fractional.L2::evict_first.b64 %0, 1.0;" : "=l"(pol));
    if (threadIdx.x < 32 * NPF && (threadIdx.x & 31) == 0) {
        const unsigned char* src = ((blockIdx.x & 4) ? Vp : Kp)
                                 + (size_t)((blockIdx.x >> 3) * 2048 + ((threadIdx.x >> 5) * 4 + (blockIdx.x & 3)) * 64) * 256;
        asm volatile("cp.async.bulk.prefetch.L2.global.L2::cache_hint [%0], %1, %2;" :: "l"(src), "r"(KVB), "l"(pol) : "memory");
    }
    extern __shared__ __align__(1024) unsigned char smem_raw[];
    uint32_t sb = smem_u32(smem_raw);
    asm volatile("" : "+r"(sb));
    sb = __shfl_sync(0xffffffffu, sb, 0);
    const uint32_t s_kv = sb + O_KV, s_q = sb + O_Q, s_e = sb + O_E, s_fin = sb + O_FIN, s_in = sb + O_IN;
    const uint32_t b_qf = sb + O_BAR, b_kvf = b_qf + 512, b_kve = b_kvf + 64, b_qe = b_kve + 64, b_fin = b_qe + 64,
                   b_in = b_fin + 64, b_e = b_in + 32;
    const int warp = __shfl_sync(0xffffffffu, threadIdx.x >> 5, 0), lane = threadIdx.x & 31;
    const int rank = blockIdx.x & (CL - 1), cid = blockIdx.x >> 3;
    const int isV = rank >> 2, part = rank & 3;
    const int kvrow = cid * 2048 + part * 64, qrow = cid * 2048 + rank * 32;
    const bool leader = elect();
    DEV_START();

    if (warp == W_PKV) {
        const CUtensorMap* mkv = isV ? &P.mv : &P.mk;
        if (leader) {
#pragma unroll
            for (int k = 0; k < 8; k++) mbar_init(b_kvf + 8 * k, 1);
        }
        __syncwarp();
        cluster_arrive();
        const uint32_t tl = tbase + kv_time(lane, isV);
#pragma unroll 1
        for (int k = 0; k < 32; k++) {
            uint32_t tt = __shfl_sync(0xffffffffu, tl, k);
            DEV_TIME(if (k >= 5) tt = tbase + (__shfl_sync(0xffffffffu, tabv, k) & 0xffff));
            const int s = k & 7;
            if (k == 8) cluster_wait();
            if (k >= 8) mbar_wait(b_kve + 8 * s, ((k >> 3) & 1) ^ 1);
            if (leader) mbar_expect_tx(b_kvf + 8 * s, KVB);
            wait_until(tt);
            if (leader) tma_load(s_kv + s * KVB, mkv, kvrow + s * 256 + (k >> 3) * HSTR, b_kvf + 8 * s, pol);
        }
        return;
    }
    if (leader) {
        if (warp == W_RED) {
            mbar_init(b_e, 1);
            asm volatile("fence.mbarrier_init.release.cluster;" ::: "memory");
            mbar_expect_tx(b_e, 8192);
            asm volatile("cp.async.bulk.tensor.3d.shared::cluster.global.mbarrier::complete_tx::bytes [%0], [%1, {%3, %4, %4}], [%2];"
                         :: "r"(s_e), "l"(isV ? &P.mf : &P.me), "r"(b_e), "r"(part * 64), "r"(0) : "memory");
        } else if (warp < 16) {
            mbar_init(b_kve + 8 * warp, warp < 8 ? 4 : 2);
#pragma unroll
            for (int i = 0; i < 4; i++) mbar_init(b_qf + 128 * i + 8 * warp, 1);
#pragma unroll
            for (int i = 0; i < 4; i++) mbar_expect_tx(b_qf + 128 * i + 8 * warp, QB / 2);
        } else if (warp < W_RED) {
            const int j = warp - W_KV;
            mbar_init(b_in + 8 * j, 1);
            mbar_init(b_fin + 16 * j, 1);
            mbar_init(b_fin + 16 * j + 8, 1);
            mbar_expect_tx(b_in + 8 * j, 4096);
            mbar_expect_tx(b_fin + 16 * j, 2048);
            mbar_expect_tx(b_fin + 16 * j + 8, 2048);
        }
    }
    __syncwarp();
    cluster_arrive();
    cluster_wait();

    if (warp == W_PQ) {
        const uint32_t tl = tbase + q_time(lane, isV);
#pragma unroll 1
        for (int b = 0; b < 32; b++) {
            uint32_t tt = __shfl_sync(0xffffffffu, tl, b);
            DEV_TIME(tt = tbase + (__shfl_sync(0xffffffffu, tabv, b) >> 16));
            const int s = b & 7;
            if (b >= 24) {
                if (b == 24) mbar_wait(b_fin + 16 * 2 + 8 * isV, 0);
                if (!(b & 1)) mbar_wait(b_kve + 8 * (s >> 1), 1);
            } else if (b >= 8) {
                mbar_wait(b_qe + 8 * s, ((b >> 3) & 1) ^ 1);
            }
            const uint32_t dst = (b >= 24 ? s_kv : s_q) + s * QB;
            const int row = qrow + s * 256 + (b >> 3) * HSTR;
            wait_until(tt);
            if (leader) {
                tma_load(dst, &P.mq, row, b_qf + 16 * b, pol);
                tma_load(dst + 4096, &P.mq, row + 16, b_qf + 16 * b + 8, pol);
            }
        }
    } else if (warp >= W_KV && warp < W_RED) {
        const int w = warp - W_KV;
        const uint32_t l7 = lane & 7;
        const uint32_t cA = (w & 1) * 4 + ((lane >> 3) & 1);
        const uint32_t a_base = s_kv + (w >> 1) * 8192 + (l7 + 8 * (lane >> 4)) * 128;
        const uint32_t a0 = a_base + ((cA ^ l7) << 4), a1 = a_base + (((cA + 2) ^ l7) << 4);
        const uint32_t e0 = s_e + l7 * 128 + (((lane >> 3) ^ l7) << 4), e1 = s_e + l7 * 128 + ((((lane >> 3) + 4) ^ l7) << 4);
        const uint32_t dst = mapa(s_in + part * 1024 + lane * 16, isV * 4 + w), rb = mapa(b_in, isV * 4 + w);
        mbar_wait(b_e, 0);
#pragma unroll 1
        for (int j = 0; j < HPC; j++) {
            float c0[4] = {0, 0, 0, 0}, c1[4] = {0, 0, 0, 0}, c2[4] = {0, 0, 0, 0}, c3[4] = {0, 0, 0, 0};
#pragma unroll 1
            for (int c = 0; c < 8; c++) {
                uint32_t e[8], a[32];
                ldsm4(e0 + c * 1024, e);
                ldsm4(e1 + c * 1024, e + 4);
                if (c == 7 && j > 0) mbar_wait_cl(b_fin + 16 * (j - 1) + 8 * isV, 0);
                mbar_wait(b_kvf + 8 * c, j & 1);
#pragma unroll
                for (int s = 0; s < 4; s++) {
                    ldsm4t(a0 + c * KVB + s * 2048, a + 8 * s);
                    ldsm4t(a1 + c * KVB + s * 2048, a + 8 * s + 4);
                }
#pragma unroll
                for (int s = 0; s < 4; s++) {
                    mma16816((s & 1) ? c2 : c0, a + 8 * s, e[2 * s], e[2 * s + 1]);
                    mma16816((s & 1) ? c3 : c1, a + 8 * s + 4, e[2 * s], e[2 * s + 1]);
                }
                __syncwarp();
                if (leader) mbar_arrive(b_kve + 8 * c);
            }
            st_async4(dst, __float_as_uint(c0[0] + c2[0]), __float_as_uint(c0[1] + c2[1]), __float_as_uint(c0[2] + c2[2]),
                      __float_as_uint(c0[3] + c2[3]), rb + 8 * j);
            st_async4(dst + 512, __float_as_uint(c1[0] + c3[0]), __float_as_uint(c1[1] + c3[1]), __float_as_uint(c1[2] + c3[2]),
                      __float_as_uint(c1[3] + c3[3]), rb + 8 * j);
        }
    } else if (warp == W_RED) {
        const uint32_t foff = s_fin + (isV ? 2048 + part * 576 : part * 512) + lane * 16;
#pragma unroll 1
        for (int j = 0; j < HPC; j++) {
            uint32_t rd[CL], rbar[CL];
#pragma unroll
            for (int r = 0; r < CL; r++) {
                rd[r] = mapa(foff + j * FINB, r);
                rbar[r] = mapa(b_fin + 16 * j + 8 * isV, r);
                asm volatile("" : "+r"(rd[r]), "+r"(rbar[r]));
            }
            mbar_wait_cl(b_in + 8 * j, 0);
            uint4 x[8];
#pragma unroll
            for (int s = 0; s < 8; s++) x[s] = lds128(s_in + s * 512 + lane * 16);
            uint32_t wv[4];
#pragma unroll
            for (int i = 0; i < 2; i++) {
#define F_(v) __uint_as_float(v)
                const float s0 = (F_(x[i].x) + F_(x[2 + i].x)) + (F_(x[4 + i].x) + F_(x[6 + i].x));
                const float s1 = (F_(x[i].y) + F_(x[2 + i].y)) + (F_(x[4 + i].y) + F_(x[6 + i].y));
                const float s2 = (F_(x[i].z) + F_(x[2 + i].z)) + (F_(x[4 + i].z) + F_(x[6 + i].z));
                const float s3 = (F_(x[i].w) + F_(x[2 + i].w)) + (F_(x[4 + i].w) + F_(x[6 + i].w));
#undef F_
                wv[2 * i] = pack_bf16(s0, s1);
                wv[2 * i + 1] = pack_bf16(s2, s3);
            }
            if (!isV) {
#pragma unroll
                for (int i = 0; i < 4; i++) asm volatile("movmatrix.sync.aligned.m8n8.trans.b16 %0, %0;" : "+r"(wv[i]));
            }
#pragma unroll
            for (int r = 0; r < CL; r++) st_async4(rd[r], wv[0], wv[1], wv[2], wv[3], rbar[r]);
        }
    } else {
        const int g = lane >> 2, t = lane & 3, op = warp >> 1, m = warp & 1;
        const uint32_t wo = warp * 4096;
        const uint32_t qx = lane & 7, qc = lane >> 4;
        const uint32_t qb0 = wo + (qx + 8 * ((lane >> 3) & 1)) * 128;
        const uint32_t voff = 2048 + (g >> 2) * 576 + t * 16 + (g & 3) * 4;
        const uint32_t sa0 = wo + 2 * t * 128 + ((g ^ (2 * t)) << 4), sa1 = wo + (2 * t + 1) * 128 + ((g ^ (2 * t + 1)) << 4);
#pragma unroll 1
        for (int j = 0; j < HPC; j++) {
            const uint32_t fin = s_fin + j * FINB;
            const uint32_t sq = j == 3 ? s_kv : s_q;
            uint32_t so0 = sq + sa0, so1 = sq + sa1, va = fin + voff, ka = fin + lane * 16;
            uint32_t qa[4];
#pragma unroll
            for (int u = 0; u < 4; u++) { qa[u] = sq + qb0 + (((2 * u + qc) ^ qx) << 4); asm volatile("" : "+r"(qa[u])); }
            asm volatile("" : "+r"(so0), "+r"(so1), "+r"(va), "+r"(ka));
            const int row = qrow + j * HSTR + op * 256 + m * 16;
            const int b = 8 * j + op;
            const uint32_t bq = b_qf + 16 * b + 8 * m;
            uint32_t a[32], vw[16];
            uint4 kf[4];
            if (b >= 1) mbar_wait(bq - 16, 0);
            mbar_wait_cl(b_fin + 16 * j, 0);
            const bool late = !mbar_test_cl(b_fin + 16 * j + 8, 0);
#pragma unroll
            for (int u = 0; u < 4; u++) kf[u] = lds128(ka + u * 512);
            if (!late) {
                acquire_cl();
#pragma unroll
                for (int x = 0; x < 16; x++) vw[x] = lds32(va + (x >> 3) * (2 * 576) + (x & 7) * 64);
            }
            mbar_wait(bq, 0);
#pragma unroll
            for (int u = 0; u < 8; u++) ldsm4(qa[u & 3] + (u >> 2) * 2048, a + 4 * u);
            float sc[4][4];
#pragma unroll
            for (int i = 0; i < 4; i++) { sc[i][0] = sc[i][1] = sc[i][2] = sc[i][3] = 0.f; }
#pragma unroll
            for (int u = 0; u < 4; u++) {
                mma16816(sc[(2 * u) & 3], a + 8 * u, kf[u].x, kf[u].y);
                mma16816(sc[(2 * u + 1) & 3], a + 8 * u + 4, kf[u].z, kf[u].w);
            }
            uint32_t p[2];
            softmax8x2((sc[0][0] + sc[1][0]) + (sc[2][0] + sc[3][0]), (sc[0][1] + sc[1][1]) + (sc[2][1] + sc[3][1]),
                       (sc[0][2] + sc[1][2]) + (sc[2][2] + sc[3][2]), (sc[0][3] + sc[1][3]) + (sc[2][3] + sc[3][3]), p[0], p[1]);
            if (late) {
                mbar_wait_cl(b_fin + 16 * j + 8, 0);
#pragma unroll
                for (int x = 0; x < 16; x++) vw[x] = lds32(va + (x >> 3) * (2 * 576) + (x & 7) * 64);
            }
#pragma unroll
            for (int H = 0; H < 2; H++) {
#pragma unroll
                for (int u = 0; u < 2; u++) {
                    uint32_t r0[4], r1[4];
#pragma unroll
                    for (int jj = 0; jj < 4; jj++) {
                        float d[4];
                        mma1688z(d, vw[8 * H + 2 * jj], vw[8 * H + 2 * jj + 1], p[u]);
                        r0[jj] = pack_bf16(d[0], d[2]);
                        r1[jj] = pack_bf16(d[1], d[3]);
                    }
                    sts128(so0 + H * 2048 + u * 1024, r0);
                    sts128(so1 + H * 2048 + u * 1024, r1);
                }
            }
            asm volatile("fence.proxy.async.shared::cta;" ::: "memory");
            __syncwarp();
            if (leader) {
                asm volatile("cp.async.bulk.tensor.3d.global.shared::cta.bulk_group [%0, {%2, %3, %2}], [%1];"
                             :: "l"(&P.mo), "r"(sq + wo), "r"(0), "r"(row) : "memory");
                if (j != 2) {
                    asm volatile("cp.async.bulk.commit_group;\ncp.async.bulk.wait_group.read 0;" ::: "memory");
                    mbar_arrive(b_qe + 8 * op);
                }
            }
        }
        DEV_END();
    }
}

typedef CUresult (*EncodeFn)(CUtensorMap*, CUtensorMapDataType, cuuint32_t, void*, const cuuint64_t*, const cuuint64_t*,
                             const cuuint32_t*, const cuuint32_t*, CUtensorMapInterleave, CUtensorMapSwizzle,
                             CUtensorMapL2promotion, CUtensorMapFloatOOBfill);

static void encode3(EncodeFn enc, CUtensorMap* m, const void* p, cuuint64_t d0, cuuint64_t d1, cuuint64_t d2,
                    cuuint64_t s1, cuuint64_t s2, cuuint32_t b1, cuuint32_t b2) {
    cuuint64_t dims[3] = {d0, d1, d2}, str[2] = {s1, s2};
    cuuint32_t box[3] = {64, b1, b2}, es[3] = {1, 1, 1};
    enc(m, CU_TENSOR_MAP_DATA_TYPE_BFLOAT16, 3, (void*)p, dims, str, box, es, CU_TENSOR_MAP_INTERLEAVE_NONE,
        CU_TENSOR_MAP_SWIZZLE_128B, CU_TENSOR_MAP_L2_PROMOTION_NONE, CU_TENSOR_MAP_FLOAT_OOB_FILL_NONE);
}

}

extern "C" void kernel_launch(void* const* d_in, const int* in_sizes, int n_in, void* d_out, int out_size) {
    static lf::EncodeFn enc = nullptr;
    if (!enc) {
        cudaDriverEntryPointQueryResult qr;
        cudaGetDriverEntryPoint("cuTensorMapEncodeTiled", (void**)&enc, cudaEnableDefault, &qr);
        cudaFuncSetAttribute(lf::lf_kernel, cudaFuncAttributeMaxDynamicSharedMemorySize, lf::SMEM);
    }
    lf::Params P;
    lf::encode3(enc, &P.mq, d_in[0], 64, 65536, 2, 256, 128, 16, 2);
    lf::encode3(enc, &P.mk, d_in[1], 64, 65536, 2, 256, 128, 64, 2);
    lf::encode3(enc, &P.mv, d_in[2], 64, 65536, 2, 256, 128, 64, 2);
    lf::encode3(enc, &P.mo, d_out, 64, 65536, 2, 256, 128, 16, 2);
    lf::encode3(enc, &P.me, d_in[3], 256, 8, 8, 4096, 512, 8, 8);
    lf::encode3(enc, &P.mf, d_in[4], 256, 8, 8, 4096, 512, 8, 8);
    lf::lf_kernel<<<64, lf::NTHREADS, lf::SMEM, cudaStreamPerThread>>>((const unsigned char*)d_in[1], (const unsigned char*)d_in[2], P);
}
```

```cpp
    return T0_ + 325 * k + 106 * hinge(k, 4) + -3 * hinge(k, 8) + (isV ? 106 : 10) * hinge(k, 16) + (isV ? -190 : 82) * hinge(k, 28);
}
__device__ __forceinline__ int q_time(int b, int isV) {
    return (isV ? 2340 : 2760) + 450 * b + (isV ? 138 : 117) * hinge(b, 8) + (isV ? -20 : -68) * hinge(b, 19)
           + (isV ? -429 : -356) * hinge(b, 21) + (isV ? 74 : 62) * hinge(b, 24) + (isV ? -7 : -6) * hinge(b, 28);
}

#define DEV_START()
#define DEV_PARAM
#define DEV_ARG
#define DEV_TIME(...)
#define DEV_END()

__global__ void __cluster_dims__(CL, 1, 1) __launch_bounds__(NTHREADS, 1)
lf_kernel(const unsigned char* __restrict__ Kp, const unsigned char* __restrict__ Vp DEV_PARAM, const __grid_constant__ Params P) {
    const uint32_t tbase = now_ns();
    uint64_t pol;
    asm volatile("createpolicy.fractional.L2::evict_first.b64 %0, 1.0;" : "=l"(pol));
    {
        const unsigned char* src = ((blockIdx.x & 4) ? Vp : Kp) + ((blockIdx.x >> 3) * (2048 * 256) + (blockIdx.x & 3) * KVB);
        if (threadIdx.x == 0) {
#pragma unroll
            for (int k = 0; k < NPF; k++)
                asm volatile("cp.async.bulk.prefetch.L2.global.L2::cache_hint [%0], %1, %2;" :: "l"(src + k * (4 * KVB)), "r"(KVB), "l"(pol) : "memory");
        }
    }
    extern __shared__ __align__(1024) unsigned char smem_raw[];
    uint32_t sb = smem_u32(smem_raw);
    asm volatile("" : "+r"(sb));
    sb = __shfl_sync(0xffffffffu, sb, 0);
    const uint32_t s_kv = sb + O_KV, s_q = sb + O_Q, s_e = sb + O_E, s_fin = sb + O_FIN, s_in = sb + O_IN;
    const uint32_t b_qf = sb + O_BAR, b_kvf = b_qf + 512, b_kve = b_kvf + 64, b_qe = b_kve + 64, b_fin = b_qe + 64,
                   b_in = b_fin + 64, b_e = b_in + 32;
    const int warp = __shfl_sync(0xffffffffu, threadIdx.x >> 5, 0), lane = threadIdx.x & 31;
    const int rank = blockIdx.x & (CL - 1), cid = blockIdx.x >> 3;
    const int isV = rank >> 2, part = rank & 3;
    const int kvrow = cid * 2048 + part * 64, qrow = cid * 2048 + rank * 32;
    const bool leader = elect();
    DEV_START();

    if (warp == W_PKV) {
        const CUtensorMap* mkv = isV ? &P.mv : &P.mk;
        if (leader) {
#pragma unroll
            for (int k = 0; k < 8; k++) mbar_init(b_kvf + 8 * k, 1);
        }
        __syncwarp();
        cluster_arrive();
        uint32_t tl = tbase + kv_time(lane, isV);
#pragma unroll 1
        for (int k = 0; k < 32; k++) {
            if (k == 5) { cluster_wait(); DEV_TIME(asm volatile("{.reg .b32 x; and.b32 x, %1, 0xffff; add.u32 %0, x, %2;}" : "=r"(tl) : "r"(tabv), "r"(tbase))); }
            const uint32_t tt = __shfl_sync(0xffffffffu, tl, k);
            const int s = k & 7;
            if (k >= 8) mbar_wait(b_kve + 8 * s, ((k >> 3) & 1) ^ 1);
            if (leader) mbar_expect_tx(b_kvf + 8 * s, KVB);
            wait_until(tt);
            if (leader) tma_load(s_kv + s * KVB, mkv, kvrow + s * 256 + (k >> 3) * HSTR, b_kvf + 8 * s, pol);
        }
        return;
    }
    if (leader) {
        if (warp == W_RED) {
            mbar_init(b_e, 1);
            asm volatile("fence.mbarrier_init.release.cluster;" ::: "memory");
            mbar_expect_tx(b_e, 8192);
            asm volatile("cp.async.bulk.tensor.3d.shared::cluster.global.mbarrier::complete_tx::bytes [%0], [%1, {%3, %4, %4}], [%2];"
                         :: "r"(s_e), "l"(isV ? &P.mf : &P.me), "r"(b_e), "r"(part * 64), "r"(0) : "memory");
        } else if (warp < 16) {
            mbar_init(b_kve + 8 * warp, warp < 8 ? 4 : 2);
#pragma unroll
            for (int i = 0; i < 4; i++) mbar_init(b_qf + 128 * i + 8 * warp, 1);
#pragma unroll
            for (int i = 0; i < 4; i++) mbar_expect_tx(b_qf + 128 * i + 8 * warp, QB / 2);
        } else if (warp < W_RED) {
            const int j = warp - W_KV;
            mbar_init(b_in + 8 * j, 1);
            mbar_init(b_fin + 16 * j, 1);
            mbar_init(b_fin + 16 * j + 8, 1);
            mbar_expect_tx(b_in + 8 * j, 4096);
            mbar_expect_tx(b_fin + 16 * j, 2048);
            mbar_expect_tx(b_fin + 16 * j + 8, 2048);
        }
    }
    __syncwarp();
    cluster_arrive();
    cluster_wait();

    if (warp == W_PQ) {
        uint32_t tl = tbase + q_time(lane, isV);
        DEV_TIME(asm volatile("{.reg .b32 x; shr.u32 x, %1, 16; add.u32 %0, x, %2;}" : "=r"(tl) : "r"(tabv), "r"(tbase)));
#pragma unroll 1
        for (int b = 0; b < 32; b++) {
            const uint32_t tt = __shfl_sync(0xffffffffu, tl, b);
            const int s = b & 7;
            if (b >= 24) {
                if (b == 24) mbar_wait(b_fin + 16 * 2 + 8 * isV, 0);
                if (!(b & 1)) mbar_wait(b_kve + 8 * (s >> 1), 1);
            } else if (b >= 8) {
                mbar_wait(b_qe + 8 * s, ((b >> 3) & 1) ^ 1);
            }
            const uint32_t dst = (b >= 24 ? s_kv : s_q) + s * QB;
            const int row = qrow + s * 256 + (b >> 3) * HSTR;
            wait_until(tt);
            if (leader) {
                tma_load(dst, &P.mq, row, b_qf + 16 * b, pol);
                tma_load(dst + 4096, &P.mq, row + 16, b_qf + 16 * b + 8, pol);
            }
        }
    } else if (warp >= W_KV && warp < W_RED) {
        const int w = warp - W_KV;
        const uint32_t l7 = lane & 7;
        const uint32_t cA = (w & 1) * 4 + ((lane >> 3) & 1);
        const uint32_t a_base = s_kv + (w >> 1) * 8192 + (l7 + 8 * (lane >> 4)) * 128;
        const uint32_t a0 = a_base + ((cA ^ l7) << 4), a1 = a_base + (((cA + 2) ^ l7) << 4);
        const uint32_t e0 = s_e + l7 * 128 + (((lane >> 3) ^ l7) << 4), e1 = s_e + l7 * 128 + ((((lane >> 3) + 4) ^ l7) << 4);
        const uint32_t dst = mapa(s_in + part * 1024 + lane * 16, isV * 4 + w), rb = mapa(b_in, isV * 4 + w);
        mbar_wait(b_e, 0);
#pragma unroll 1
        for (int j = 0; j < HPC; j++) {
            float c0[4] = {0, 0, 0, 0}, c1[4] = {0, 0, 0, 0}, c2[4] = {0, 0, 0, 0}, c3[4] = {0, 0, 0, 0};
#pragma unroll 1
            for (int c = 0; c < 8; c++) {
                uint32_t e[8], a[32];
                ldsm4(e0 + c * 1024, e);
                ldsm4(e1 + c * 1024, e + 4);
                if (c == 7 && j > 0) mbar_wait_cl(b_fin + 16 * (j - 1) + 8 * isV, 0);
                mbar_wait(b_kvf + 8 * c, j & 1);
#pragma unroll
                for (int s = 0; s < 4; s++) {
                    ldsm4t(a0 + c * KVB + s * 2048, a + 8 * s);
                    ldsm4t(a1 + c * KVB + s * 2048, a + 8 * s + 4);
                }
#pragma unroll
                for (int s = 0; s < 4; s++) {
                    mma16816((s & 1) ? c2 : c0, a + 8 * s, e[2 * s], e[2 * s + 1]);
                    mma16816((s & 1) ? c3 : c1, a + 8 * s + 4, e[2 * s], e[2 * s + 1]);
                }
                __syncwarp();
                if (leader) mbar_arrive(b_kve + 8 * c);
            }
            st_async4(dst, __float_as_uint(c0[0] + c2[0]), __float_as_uint(c0[1] + c2[1]), __float_as_uint(c0[2] + c2[2]),
                      __float_as_uint(c0[3] + c2[3]), rb + 8 * j);
            st_async4(dst + 512, __float_as_uint(c1[0] + c3[0]), __float_as_uint(c1[1] + c3[1]), __float_as_uint(c1[2] + c3[2]),
                      __float_as_uint(c1[3] + c3[3]), rb + 8 * j);
        }
    } else if (warp == W_RED) {
        const uint32_t foff = s_fin + (isV ? 2048 + part * 576 : part * 512) + lane * 16;
#pragma unroll 1
        for (int j = 0; j < HPC; j++) {
            uint32_t rd[CL], rbar[CL];
#pragma unroll
            for (int r = 0; r < CL; r++) {
                rd[r] = mapa(foff + j * FINB, r);
                rbar[r] = mapa(b_fin + 16 * j + 8 * isV, r);
                asm volatile("" : "+r"(rd[r]), "+r"(rbar[r]));
            }
            mbar_wait_cl(b_in + 8 * j, 0);
            uint4 x[8];
#pragma unroll
            for (int s = 0; s < 8; s++) x[s] = lds128(s_in + s * 512 + lane * 16);
            uint32_t wv[4];
#pragma unroll
            for (int i = 0; i < 2; i++) {
#define F_(v) __uint_as_float(v)
                const float s0 = (F_(x[i].x) + F_(x[2 + i].x)) + (F_(x[4 + i].x) + F_(x[6 + i].x));
                const float s1 = (F_(x[i].y) + F_(x[2 + i].y)) + (F_(x[4 + i].y) + F_(x[6 + i].y));
                const float s2 = (F_(x[i].z) + F_(x[2 + i].z)) + (F_(x[4 + i].z) + F_(x[6 + i].z));
                const float s3 = (F_(x[i].w) + F_(x[2 + i].w)) + (F_(x[4 + i].w) + F_(x[6 + i].w));
#undef F_
                wv[2 * i] = pack_bf16(s0, s1);
                wv[2 * i + 1] = pack_bf16(s2, s3);
            }
            if (!isV) {
#pragma unroll
                for (int i = 0; i < 4; i++) asm volatile("movmatrix.sync.aligned.m8n8.trans.b16 %0, %0;" : "+r"(wv[i]));
            }
#pragma unroll
            for (int r = 0; r < CL; r++) st_async4(rd[r], wv[0], wv[1], wv[2], wv[3], rbar[r]);
        }
    } else {
        const int g = lane >> 2, t = lane & 3, op = warp >> 1, m = warp & 1;
        const uint32_t wo = warp * 4096;
        const uint32_t qx = lane & 7, qc = lane >> 4;
        const uint32_t qb0 = wo + (qx + 8 * ((lane >> 3) & 1)) * 128;
        const uint32_t voff = 2048 + (g >> 2) * 576 + t * 16 + (g & 3) * 4;
        const uint32_t sa0 = wo + 2 * t * 128 + ((g ^ (2 * t)) << 4), sa1 = wo + (2 * t + 1) * 128 + ((g ^ (2 * t + 1)) << 4);
#pragma unroll 1
        for (int j = 0; j < HPC; j++) {
            const uint32_t fin = s_fin + j * FINB;
            const uint32_t sq = j == 3 ? s_kv : s_q;
            uint32_t so0 = sq + sa0, so1 = sq + sa1, va = fin + voff, ka = fin + lane * 16;
            uint32_t qa[4];
#pragma unroll
            for (int u = 0; u < 4; u++) { qa[u] = sq + qb0 + (((2 * u + qc) ^ qx) << 4); asm volatile("" : "+r"(qa[u])); }
            asm volatile("" : "+r"(so0), "+r"(so1), "+r"(va), "+r"(ka));
            const int row = qrow + j * HSTR + op * 256 + m * 16;
            const int b = 8 * j + op;
            const uint32_t bq = b_qf + 16 * b + 8 * m;
            uint32_t a[32], vw[16];
            uint4 kf[4];
            if (b >= 1) mbar_wait(bq - 16, 0);
            mbar_wait_cl(b_fin + 16 * j, 0);
            const bool late = !mbar_test_cl(b_fin + 16 * j + 8, 0);
#pragma unroll
            for (int u = 0; u < 4; u++) kf[u] = lds128(ka + u * 512);
            if (!late) {
                acquire_cl();
#pragma unroll
                for (int x = 0; x < 16; x++) vw[x] = lds32(va + (x >> 3) * (2 * 576) + (x & 7) * 64);
            }
            mbar_wait(bq, 0);
#pragma unroll
            for (int u = 0; u < 8; u++) ldsm4(qa[u & 3] + (u >> 2) * 2048, a + 4 * u);
            float sc[4][4];
#pragma unroll
            for (int i = 0; i < 4; i++) { sc[i][0] = sc[i][1] = sc[i][2] = sc[i][3] = 0.f; }
#pragma unroll
            for (int u = 0; u < 4; u++) {
                mma16816(sc[(2 * u) & 3], a + 8 * u, kf[u].x, kf[u].y);
                mma16816(sc[(2 * u + 1) & 3], a + 8 * u + 4, kf[u].z, kf[u].w);
            }
            uint32_t p[2];
            softmax8x2((sc[0][0] + sc[1][0]) + (sc[2][0] + sc[3][0]), (sc[0][1] + sc[1][1]) + (sc[2][1] + sc[3][1]),
                       (sc[0][2] + sc[1][2]) + (sc[2][2] + sc[3][2]), (sc[0][3] + sc[1][3]) + (sc[2][3] + sc[3][3]), p[0], p[1]);
            if (late) {
                mbar_wait_cl(b_fin + 16 * j + 8, 0);
#pragma unroll
                for (int x = 0; x < 16; x++) vw[x] = lds32(va + (x >> 3) * (2 * 576) + (x & 7) * 64);
            }
#pragma unroll
            for (int H = 0; H < 2; H++) {
#pragma unroll
                for (int u = 0; u < 2; u++) {
                    uint32_t r0[4], r1[4];
#pragma unroll
                    for (int jj = 0; jj < 4; jj++) {
                        float d[4];
                        mma1688z(d, vw[8 * H + 2 * jj], vw[8 * H + 2 * jj + 1], p[u]);
                        r0[jj] = pack_bf16(d[0], d[2]);
                        r1[jj] = pack_bf16(d[1], d[3]);
                    }
                    sts128(so0 + H * 2048 + u * 1024, r0);
                    sts128(so1 + H * 2048 + u * 1024, r1);
                }
            }
            asm volatile("fence.proxy.async.shared::cta;" ::: "memory");
            __syncwarp();
            if (leader) {
                asm volatile("cp.async.bulk.tensor.3d.global.shared::cta.bulk_group [%0, {%2, %3, %2}], [%1];"
                             :: "l"(&P.mo), "r"(sq + wo), "r"(0), "r"(row) : "memory");
                if (j != 2) {
                    asm volatile("cp.async.bulk.commit_group;\ncp.async.bulk.wait_group.read 0;" ::: "memory");
                    mbar_arrive(b_qe + 8 * op);
                }
            }
        }
        DEV_END();
    }
}

typedef CUresult (*EncodeFn)(CUtensorMap*, CUtensorMapDataType, cuuint32_t, void*, const cuuint64_t*, const cuuint64_t*,
                             const cuuint32_t*, const cuuint32_t*, CUtensorMapInterleave, CUtensorMapSwizzle,
                             CUtensorMapL2promotion, CUtensorMapFloatOOBfill);

static void encode3(EncodeFn enc, CUtensorMap* m, const void* p, cuuint64_t d0, cuuint64_t d1, cuuint64_t d2,
                    cuuint64_t s1, cuuint64_t s2, cuuint32_t b1, cuuint32_t b2) {
    cuuint64_t dims[3] = {d0, d1, d2}, str[2] = {s1, s2};
    cuuint32_t box[3] = {64, b1, b2}, es[3] = {1, 1, 1};
    enc(m, CU_TENSOR_MAP_DATA_TYPE_BFLOAT16, 3, (void*)p, dims, str, box, es, CU_TENSOR_MAP_INTERLEAVE_NONE,
        CU_TENSOR_MAP_SWIZZLE_128B, CU_TENSOR_MAP_L2_PROMOTION_NONE, CU_TENSOR_MAP_FLOAT_OOB_FILL_NONE);
}

}

extern "C" void kernel_launch(void* const* d_in, const int* in_sizes, int n_in, void* d_out, int out_size) {
    static lf::EncodeFn enc = nullptr;
    if (!enc) {
        cudaDriverEntryPointQueryResult qr;
        cudaGetDriverEntryPoint("cuTensorMapEncodeTiled", (void**)&enc, cudaEnableDefault, &qr);
        cudaFuncSetAttribute(lf::lf_kernel, cudaFuncAttributeMaxDynamicSharedMemorySize, lf::SMEM);
    }
    lf::Params P;
    lf::encode3(enc, &P.mq, d_in[0], 64, 65536, 2, 256, 128, 16, 2);
    lf::encode3(enc, &P.mk, d_in[1], 64, 65536, 2, 256, 128, 64, 2);
    lf::encode3(enc, &P.mv, d_in[2], 64, 65536, 2, 256, 128, 64, 2);
    lf::encode3(enc, &P.mo, d_out, 64, 65536, 2, 256, 128, 16, 2);
    lf::encode3(enc, &P.me, d_in[3], 256, 8, 8, 4096, 512, 8, 8);
    lf::encode3(enc, &P.mf, d_in[4], 256, 8, 8, 4096, 512, 8, 8);
    lf::lf_kernel<<<64, lf::NTHREADS, lf::SMEM, cudaStreamPerThread>>>((const unsigned char*)d_in[1], (const unsigned char*)d_in[2] DEV_ARG, P);
}
```

```cpp
    return -475 + 325 * k + 89 * hinge(k, 4) + 21 * hinge(k, 8) + (isV ? 107 : -5) * hinge(k, 16) + (isV ? -65 : 74) * hinge(k, 24) + (isV ? -74 : -45) * hinge(k, 28);
}
__device__ __forceinline__ int q_time(int b, int isV) {
    return (isV ? 2350 : 2690) + 466 * b + (isV ? 124 : 103) * hinge(b, 8) + (isV ? -133 : -170) * hinge(b, 20) + (isV ? -305 : -247) * hinge(b, 21) + 22 * hinge(b, 24) + 26 * hinge(b, 26);
}

__global__ void __cluster_dims__(CL, 1, 1) __launch_bounds__(NTHREADS, 1)
lf_kernel(const unsigned char* __restrict__ Kp, const unsigned char* __restrict__ Vp, const __grid_constant__ Params P) {
    const uint32_t tbase = now_ns();
    uint64_t pol;
    asm volatile("createpolicy.fractional.L2::evict_first.b64 %0, 1.0;" : "=l"(pol));
    {
        const unsigned char* src = ((blockIdx.x & 4) ? Vp : Kp) + ((blockIdx.x >> 3) * (2048 * 256) + (blockIdx.x & 3) * KVB);
        if (threadIdx.x == 0) {
#pragma unroll
            for (int k = 0; k < NPF; k++)
                asm volatile("cp.async.bulk.prefetch.L2.global.L2::cache_hint [%0], %1, %2;" :: "l"(src + kv_block(k) * (4 * KVB)), "r"(KVB), "l"(pol) : "memory");
        }
    }
    extern __shared__ __align__(1024) unsigned char smem_raw[];
    uint32_t sb = smem_u32(smem_raw);
    asm volatile("" : "+r"(sb));
    sb = __shfl_sync(0xffffffffu, sb, 0);
    const uint32_t s_kv = sb + O_KV, s_q = sb + O_Q, s_e = sb + O_E, s_fin = sb + O_FIN, s_in = sb + O_IN;
    const uint32_t b_qf = sb + O_BAR, b_kvf = b_qf + 512, b_kve = b_kvf + 64, b_qe = b_kve + 64, b_fin = b_qe + 64,
                   b_in = b_fin + 64, b_e = b_in + 32;
    const int warp = __shfl_sync(0xffffffffu, threadIdx.x >> 5, 0), lane = threadIdx.x & 31;
    const int rank = blockIdx.x & (CL - 1), cid = blockIdx.x >> 3;
    const int isV = rank >> 2, part = rank & 3;
    const int kvrow = cid * 2048 + part * 64, qrow = cid * 2048 + rank * 32;
    const bool leader = elect();

    if (warp == W_PKV) {
        const CUtensorMap* mkv = isV ? &P.mv : &P.mk;
        if (leader) {
#pragma unroll
            for (int k = 0; k < 8; k++) mbar_init(b_kvf + 8 * k, 1);
        }
        __syncwarp();
        cluster_arrive();
        const uint32_t tl = tbase + kv_time(lane, isV);
#pragma unroll 1
        for (int k = 0; k < 32; k++) {
            if (k == 5) cluster_wait();
            const uint32_t tt = __shfl_sync(0xffffffffu, tl, k);
            const int s = k & 7;
            if (k >= 8) mbar_wait(b_kve + 8 * s, ((k >> 3) & 1) ^ 1);
            if (leader) mbar_expect_tx(b_kvf + 8 * s, KVB);
            wait_until(tt);
            if (leader) tma_load(s_kv + s * KVB, mkv, kvrow + kv_block(s) * 256 + (k >> 3) * HSTR, b_kvf + 8 * s, pol);
        }
        return;
    }
    if (leader) {
        if (warp == W_RED) {
            mbar_init(b_e, 1);
            asm volatile("fence.mbarrier_init.release.cluster;" ::: "memory");
            mbar_expect_tx(b_e, 8192);
            asm volatile("cp.async.bulk.tensor.3d.shared::cluster.global.mbarrier::complete_tx::bytes [%0], [%1, {%3, %4, %4}], [%2];"
                         :: "r"(s_e), "l"(isV ? &P.mf : &P.me), "r"(b_e), "r"(part * 64), "r"(0) : "memory");
        } else if (warp < 16) {
            mbar_init(b_kve + 8 * warp, warp < 8 ? 4 : 2);
#pragma unroll
            for (int i = 0; i < 4; i++) mbar_init(b_qf + 128 * i + 8 * warp, 1);
#pragma unroll
            for (int i = 0; i < 4; i++) mbar_expect_tx(b_qf + 128 * i + 8 * warp, QB / 2);
        } else if (warp < W_RED) {
            const int j = warp - W_KV;
            mbar_init(b_in + 8 * j, 1);
            mbar_init(b_fin + 16 * j, 1);
            mbar_init(b_fin + 16 * j + 8, 1);
            mbar_expect_tx(b_in + 8 * j, 4096);
            mbar_expect_tx(b_fin + 16 * j, 2048);
            mbar_expect_tx(b_fin + 16 * j + 8, 2048);
        }
    }
    __syncwarp();
    cluster_arrive();
    cluster_wait();

    if (warp == W_PQ) {
        const uint32_t tl = tbase + q_time(lane, isV);
#pragma unroll 1
        for (int b = 0; b < 32; b++) {
            const uint32_t tt = __shfl_sync(0xffffffffu, tl, b);
            const int s = b & 7;
            if (b == 20) {
#pragma unroll
                for (int i = 4; i < 8; i++) mbar_wait(b_qe + 8 * i, 1);
            } else if (b == 21) {
                mbar_wait(b_fin + 16 * 2 + 8 * isV, 0);
                mbar_wait(b_kve + 8 * 3, 1);
            } else if (b >= 8 && b < 20) {
                mbar_wait(b_qe + 8 * s, ((b >> 3) & 1) ^ 1);
            }
            const uint32_t dst = (b >= 24 ? s_kv : s_q) + s * QB;
            const int row = qrow + s * 256 + (b >> 3) * HSTR;
            wait_until(tt);
            if (leader) {
                tma_load(dst, &P.mq, row, b_qf + 16 * b, pol);
                tma_load(dst + 4096, &P.mq, row + 16, b_qf + 16 * b + 8, pol);
            }
        }
    } else if (warp >= W_KV && warp < W_RED) {
        const int w = warp - W_KV;
        const uint32_t l7 = lane & 7;
        const uint32_t cA = (w & 1) * 4 + ((lane >> 3) & 1);
        const uint32_t a_base = s_kv + (w >> 1) * 8192 + (l7 + 8 * (lane >> 4)) * 128;
        const uint32_t a0 = a_base + ((cA ^ l7) << 4), a1 = a_base + (((cA + 2) ^ l7) << 4);
        const uint32_t e0 = s_e + l7 * 128 + (((lane >> 3) ^ l7) << 4), e1 = s_e + l7 * 128 + ((((lane >> 3) + 4) ^ l7) << 4);
        const uint32_t dst = mapa(s_in + part * 1024 + lane * 16, isV * 4 + w), rb = mapa(b_in, isV * 4 + w);
        mbar_wait(b_e, 0);
#pragma unroll 1
        for (int j = 0; j < HPC; j++) {
            float c0[4] = {0, 0, 0, 0}, c1[4] = {0, 0, 0, 0}, c2[4] = {0, 0, 0, 0}, c3[4] = {0, 0, 0, 0};
#pragma unroll 1
            for (int c = 0; c < 8; c++) {
                uint32_t e[8], a[32];
                ldsm4(e0 + kv_block(c) * 1024, e);
                ldsm4(e1 + kv_block(c) * 1024, e + 4);
                if (c == 7 && j > 0) mbar_wait_cl(b_fin + 16 * (j - 1) + 8 * isV, 0);
                mbar_wait(b_kvf + 8 * c, j & 1);
#pragma unroll
                for (int s = 0; s < 4; s++) {
                    ldsm4t(a0 + c * KVB + s * 2048, a + 8 * s);
                    ldsm4t(a1 + c * KVB + s * 2048, a + 8 * s + 4);
                }
#pragma unroll
                for (int s = 0; s < 4; s++) {
                    mma16816((s & 1) ? c2 : c0, a + 8 * s, e[2 * s], e[2 * s + 1]);
                    mma16816((s & 1) ? c3 : c1, a + 8 * s + 4, e[2 * s], e[2 * s + 1]);
                }
                __syncwarp();
                if (leader) mbar_arrive(b_kve + 8 * c);
            }
            st_async4(dst, __float_as_uint(c0[0] + c2[0]), __float_as_uint(c0[1] + c2[1]), __float_as_uint(c0[2] + c2[2]),
                      __float_as_uint(c0[3] + c2[3]), rb + 8 * j);
            st_async4(dst + 512, __float_as_uint(c1[0] + c3[0]), __float_as_uint(c1[1] + c3[1]), __float_as_uint(c1[2] + c3[2]),
                      __float_as_uint(c1[3] + c3[3]), rb + 8 * j);
        }
    } else if (warp == W_RED) {
        const uint32_t foff = s_fin + (isV ? 2048 + part * 576 : part * 512) + lane * 16;
#pragma unroll 1
        for (int j = 0; j < HPC; j++) {
            uint32_t rd[CL], rbar[CL];
#pragma unroll
            for (int r = 0; r < CL; r++) {
                rd[r] = mapa(foff + j * FINB, r);
                rbar[r] = mapa(b_fin + 16 * j + 8 * isV, r);
                asm volatile("" : "+r"(rd[r]), "+r"(rbar[r]));
            }
            mbar_wait_cl(b_in + 8 * j, 0);
            uint4 x[8];
#pragma unroll
            for (int s = 0; s < 8; s++) x[s] = lds128(s_in + s * 512 + lane * 16);
            uint32_t wv[4];
#pragma unroll
            for (int i = 0; i < 2; i++) {
#define F_(v) __uint_as_float(v)
                const float s0 = (F_(x[i].x) + F_(x[2 + i].x)) + (F_(x[4 + i].x) + F_(x[6 + i].x));
                const float s1 = (F_(x[i].y) + F_(x[2 + i].y)) + (F_(x[4 + i].y) + F_(x[6 + i].y));
                const float s2 = (F_(x[i].z) + F_(x[2 + i].z)) + (F_(x[4 + i].z) + F_(x[6 + i].z));
                const float s3 = (F_(x[i].w) + F_(x[2 + i].w)) + (F_(x[4 + i].w) + F_(x[6 + i].w));
#undef F_
                wv[2 * i] = pack_bf16(s0, s1);
                wv[2 * i + 1] = pack_bf16(s2, s3);
            }
            if (!isV) {
#pragma unroll
                for (int i = 0; i < 4; i++) asm volatile("movmatrix.sync.aligned.m8n8.trans.b16 %0, %0;" : "+r"(wv[i]));
            }
#pragma unroll
            for (int r = 0; r < CL; r++) st_async4(rd[r], wv[0], wv[1], wv[2], wv[3], rbar[r]);
        }
    } else {
        const int g = lane >> 2, t = lane & 3, op = warp >> 1, m = warp & 1;
        const uint32_t wo = warp * 4096;
        const uint32_t qx = lane & 7, qc = lane >> 4;
        const uint32_t qb0 = wo + (qx + 8 * ((lane >> 3) & 1)) * 128;
        const uint32_t voff = 2048 + (g >> 2) * 576 + t * 16 + (g & 3) * 4;
        const uint32_t sa0 = wo + 2 * t * 128 + ((g ^ (2 * t)) << 4), sa1 = wo + (2 * t + 1) * 128 + ((g ^ (2 * t + 1)) << 4);
#pragma unroll 1
        for (int j = 0; j < HPC; j++) {
            const uint32_t fin = s_fin + j * FINB;
            const uint32_t sq = j == 3 ? s_kv : s_q;
            uint32_t so0 = sq + sa0, so1 = sq + sa1, va = fin + voff, ka = fin + lane * 16;
            uint32_t qa[4];
#pragma unroll
            for (int u = 0; u < 4; u++) { qa[u] = sq + qb0 + (((2 * u + qc) ^ qx) << 4); asm volatile("" : "+r"(qa[u])); }
            asm volatile("" : "+r"(so0), "+r"(so1), "+r"(va), "+r"(ka));
            const int row = qrow + j * HSTR + op * 256 + m * 16;
            const int b = 8 * j + op;
            const uint32_t bq = b_qf + 16 * b + 8 * m;
            uint32_t a[32], vw[16];
            uint4 kf[4];
            if (b >= 1) mbar_wait(bq - 16, 0);
            mbar_wait_cl(b_fin + 16 * j, 0);
            const bool late = !mbar_test_cl(b_fin + 16 * j + 8, 0);
#pragma unroll
            for (int u = 0; u < 4; u++) kf[u] = lds128(ka + u * 512);
            if (!late) {
                acquire_cl();
#pragma unroll
                for (int x = 0; x < 16; x++) vw[x] = lds32(va + (x >> 3) * (2 * 576) + (x & 7) * 64);
            }
            mbar_wait(bq, 0);
#pragma unroll
            for (int u = 0; u < 8; u++) ldsm4(qa[u & 3] + (u >> 2) * 2048, a + 4 * u);
            float sc[4][4];
#pragma unroll
            for (int i = 0; i < 4; i++) { sc[i][0] = sc[i][1] = sc[i][2] = sc[i][3] = 0.f; }
#pragma unroll
            for (int u = 0; u < 4; u++) {
                mma16816(sc[(2 * u) & 3], a + 8 * u, kf[u].x, kf[u].y);
                mma16816(sc[(2 * u + 1) & 3], a + 8 * u + 4, kf[u].z, kf[u].w);
            }
            uint32_t p[2];
            softmax8x2((sc[0][0] + sc[1][0]) + (sc[2][0] + sc[3][0]), (sc[0][1] + sc[1][1]) + (sc[2][1] + sc[3][1]),
                       (sc[0][2] + sc[1][2]) + (sc[2][2] + sc[3][2]), (sc[0][3] + sc[1][3]) + (sc[2][3] + sc[3][3]), p[0], p[1]);
            if (late) {
                mbar_wait_cl(b_fin + 16 * j + 8, 0);
#pragma unroll
                for (int x = 0; x < 16; x++) vw[x] = lds32(va + (x >> 3) * (2 * 576) + (x & 7) * 64);
            }
#pragma unroll
            for (int H = 0; H < 2; H++) {
#pragma unroll
                for (int u = 0; u < 2; u++) {
                    uint32_t r0[4], r1[4];
#pragma unroll
                    for (int jj = 0; jj < 4; jj++) {
                        float d[4];
                        mma1688z(d, vw[8 * H + 2 * jj], vw[8 * H + 2 * jj + 1], p[u]);
                        r0[jj] = pack_bf16(d[0], d[2]);
                        r1[jj] = pack_bf16(d[1], d[3]);
                    }
                    sts128(so0 + H * 2048 + u * 1024, r0);
                    sts128(so1 + H * 2048 + u * 1024, r1);
                }
            }
            asm volatile("fence.proxy.async.shared::cta;" ::: "memory");
            __syncwarp();
            if (leader) {
                asm volatile("cp.async.bulk.tensor.3d.global.shared::cta.bulk_group [%0, {%2, %3, %2}], [%1];"
                             :: "l"(&P.mo), "r"(sq + wo), "r"(0), "r"(row) : "memory");
                if (j != 2) {
                    asm volatile("cp.async.bulk.commit_group;\ncp.async.bulk.wait_group.read 0;" ::: "memory");
                    mbar_arrive(b_qe + 8 * op);
                }
            }
        }
    }
}

typedef CUresult (*EncodeFn)(CUtensorMap*, CUtensorMapDataType, cuuint32_t, void*, const cuuint64_t*, const cuuint64_t*,
                             const cuuint32_t*, const cuuint32_t*, CUtensorMapInterleave, CUtensorMapSwizzle,
                             CUtensorMapL2promotion, CUtensorMapFloatOOBfill);

static void encode3(EncodeFn enc, CUtensorMap* m, const void* p, cuuint64_t d0, cuuint64_t d1, cuuint64_t d2,
                    cuuint64_t s1, cuuint64_t s2, cuuint32_t b1, cuuint32_t b2) {
    cuuint64_t dims[3] = {d0, d1, d2}, str[2] = {s1, s2};
    cuuint32_t box[3] = {64, b1, b2}, es[3] = {1, 1, 1};
    enc(m, CU_TENSOR_MAP_DATA_TYPE_BFLOAT16, 3, (void*)p, dims, str, box, es, CU_TENSOR_MAP_INTERLEAVE_NONE,
        CU_TENSOR_MAP_SWIZZLE_128B, CU_TENSOR_MAP_L2_PROMOTION_NONE, CU_TENSOR_MAP_FLOAT_OOB_FILL_NONE);
}

}

extern "C" void kernel_launch(void* const* d_in, const int* in_sizes, int n_in, void* d_out, int out_size) {
    static lf::EncodeFn enc = nullptr;
    if (!enc) {
        cudaDriverEntryPointQueryResult qr;
        cudaGetDriverEntryPoint("cuTensorMapEncodeTiled", (void**)&enc, cudaEnableDefault, &qr);
        cudaFuncSetAttribute(lf::lf_kernel, cudaFuncAttributeMaxDynamicSharedMemorySize, lf::SMEM);
    }
    lf::Params P;
    lf::encode3(enc, &P.mq, d_in[0], 64, 65536, 2, 256, 128, 16, 2);
    lf::encode3(enc, &P.mk, d_in[1], 64, 65536, 2, 256, 128, 64, 2);
    lf::encode3(enc, &P.mv, d_in[2], 64, 65536, 2, 256, 128, 64, 2);
    lf::encode3(enc, &P.mo, d_out, 64, 65536, 2, 256, 128, 16, 2);
    lf::encode3(enc, &P.me, d_in[3], 256, 8, 8, 4096, 512, 8, 8);
    lf::encode3(enc, &P.mf, d_in[4], 256, 8, 8, 4096, 512, 8, 8);
    lf::lf_kernel<<<64, lf::NTHREADS, lf::SMEM, cudaStreamPerThread>>>((const unsigned char*)d_in[1], (const unsigned char*)d_in[2], P);
}
```

```cpp
#include <cuda_runtime.h>
#include <cuda_bf16.h>
#include <cuda.h>
#include <stdint.h>

namespace lf {

__device__ __forceinline__ uint32_t smem_u32(const void* p) { return (uint32_t)__cvta_generic_to_shared(p); }
__device__ __forceinline__ void mbar_init(uint32_t bar, uint32_t cnt) {
    asm volatile("mbarrier.init.shared::cta.b64 [%0], %1;" :: "r"(bar), "r"(cnt) : "memory");
}
__device__ __forceinline__ void mbar_expect_tx(uint32_t bar, uint32_t bytes) {
    asm volatile("mbarrier.arrive.expect_tx.shared::cta.b64 _, [%0], %1;" :: "r"(bar), "r"(bytes) : "memory");
}
__device__ __forceinline__ void mbar_arrive(uint32_t bar) {
    asm volatile("mbarrier.arrive.shared::cta.b64 _, [%0];" :: "r"(bar) : "memory");
}
__device__ __forceinline__ bool mbar_try(uint32_t bar, uint32_t parity) {
    uint32_t ok;
    asm volatile("{\n.reg .pred p;\nmbarrier.try_wait.parity.shared::cta.b64 p, [%1], %2;\nselp.u32 %0, 1, 0, p;\n}"
                 : "=r"(ok) : "r"(bar), "r"(parity) : "memory");
    return ok;
}
__device__ __forceinline__ bool mbar_try_cl(uint32_t bar, uint32_t parity) {
    uint32_t ok;
    asm volatile("{\n.reg .pred p;\nmbarrier.try_wait.parity.relaxed.cluster.shared::cta.b64 p, [%1], %2;\nselp.u32 %0, 1, 0, p;\n}"
                 : "=r"(ok) : "r"(bar), "r"(parity) : "memory");
    return ok;
}
__device__ __forceinline__ bool mbar_test_cl(uint32_t bar, uint32_t parity) {
    uint32_t ok;
    asm volatile("{\n.reg .pred p;\nmbarrier.test_wait.parity.relaxed.cluster.shared::cta.b64 p, [%1], %2;\nselp.u32 %0, 1, 0, p;\n}"
                 : "=r"(ok) : "r"(bar), "r"(parity) : "memory");
    return ok;
}
__device__ __forceinline__ void acquire_cl() { asm volatile("fence.acquire.sync_restrict::shared::cluster.cluster;" ::: "memory"); }
__device__ __forceinline__ void mbar_wait(uint32_t bar, uint32_t parity) {
    int n = 0;
    while (!mbar_try(bar, parity)) { if (++n > (1 << 20)) __trap(); }
}
__device__ __forceinline__ void mbar_wait_cl(uint32_t bar, uint32_t parity) {
    int n = 0;
    while (!mbar_try_cl(bar, parity)) { if (++n > (1 << 20)) __trap(); }
    acquire_cl();
}
__device__ __forceinline__ uint32_t now_ns() { uint32_t t; asm volatile("mov.u32 %0, %%globaltimer_lo;" : "=r"(t)); return t; }
__device__ __forceinline__ void wait_until(uint32_t t) {
    for (int n = 0; (int)(now_ns() - t) < 0 && n < 4096; n++) { }
}
__device__ __forceinline__ void tma_load(uint32_t dst, const CUtensorMap* m, int row, uint32_t bar, uint64_t pol) {
    asm volatile("cp.async.bulk.tensor.3d.shared::cluster.global.mbarrier::complete_tx::bytes.L2::cache_hint [%0], [%1, {%3, %4, %3}], [%2], %5;"
                 :: "r"(dst), "l"(m), "r"(bar), "r"(0), "r"(row), "l"(pol) : "memory");
}
__device__ __forceinline__ void ldsm4(uint32_t a, uint32_t* r) {
    asm volatile("ldmatrix.sync.aligned.m8n8.x4.shared.b16 {%0,%1,%2,%3}, [%4];" : "=r"(r[0]), "=r"(r[1]), "=r"(r[2]), "=r"(r[3]) : "r"(a) : "memory");
}
__device__ __forceinline__ void ldsm4t(uint32_t a, uint32_t* r) {
    asm volatile("ldmatrix.sync.aligned.m8n8.x4.trans.shared.b16 {%0,%1,%2,%3}, [%4];" : "=r"(r[0]), "=r"(r[1]), "=r"(r[2]), "=r"(r[3]) : "r"(a) : "memory");
}
__device__ __forceinline__ void mma16816(float* c, const uint32_t* a, uint32_t b0, uint32_t b1) {
    asm volatile("mma.sync.aligned.m16n8k16.row.col.f32.bf16.bf16.f32 {%0,%1,%2,%3}, {%4,%5,%6,%7}, {%8,%9}, {%0,%1,%2,%3};"
                 : "+f"(c[0]), "+f"(c[1]), "+f"(c[2]), "+f"(c[3]) : "r"(a[0]), "r"(a[1]), "r"(a[2]), "r"(a[3]), "r"(b0), "r"(b1));
}
__device__ __forceinline__ void mma1688z(float* d, uint32_t a0, uint32_t a1, uint32_t b0) {
    asm volatile("mma.sync.aligned.m16n8k8.row.col.f32.bf16.bf16.f32 {%0,%1,%2,%3}, {%4,%5}, {%6}, {%7,%7,%7,%7};"
                 : "=f"(d[0]), "=f"(d[1]), "=f"(d[2]), "=f"(d[3]) : "r"(a0), "r"(a1), "r"(b0), "f"(0.f));
}
__device__ __forceinline__ uint32_t pack_bf16(float lo, float hi) { uint32_t r; asm("cvt.rn.bf16x2.f32 %0, %1, %2;" : "=r"(r) : "f"(hi), "f"(lo)); return r; }
__device__ __forceinline__ float bf_lo(uint32_t x) { return __uint_as_float(x << 16); }
__device__ __forceinline__ float bf_hi(uint32_t x) { return __uint_as_float(x & 0xffff0000u); }
__device__ __forceinline__ uint32_t bfmax2(uint32_t a, uint32_t b) { uint32_t d; asm("max.bf16x2 %0, %1, %2;" : "=r"(d) : "r"(a), "r"(b)); return d; }
__device__ __forceinline__ float ex2(float x) { float y; asm("ex2.approx.ftz.f32 %0, %1;" : "=f"(y) : "f"(x)); return y; }
__device__ __forceinline__ float rcp(float x) { float y; asm("rcp.approx.ftz.f32 %0, %1;" : "=f"(y) : "f"(x)); return y; }
__device__ __forceinline__ uint32_t mapa(uint32_t a, uint32_t r) { uint32_t d; asm("mapa.shared::cluster.u32 %0, %1, %2;" : "=r"(d) : "r"(a), "r"(r)); return d; }
__device__ __forceinline__ bool elect() {
    uint32_t p;
    asm volatile("{\n.reg .pred p;\nelect.sync _|p, 0xffffffff;\nselp.u32 %0, 1, 0, p;\n}" : "=r"(p));
    return p;
}
__device__ __forceinline__ void st_async4(uint32_t dst, uint32_t a, uint32_t b, uint32_t c, uint32_t d, uint32_t bar) {
    asm volatile("st.async.weak.shared::cluster.mbarrier::complete_tx::bytes.v4.b32 [%0], {%1,%2,%3,%4}, [%5];"
                 :: "r"(dst), "r"(a), "r"(b), "r"(c), "r"(d), "r"(bar) : "memory");
}
__device__ __forceinline__ uint4 lds128(uint32_t a) {
    uint4 v; asm volatile("ld.shared.v4.b32 {%0,%1,%2,%3}, [%4];" : "=r"(v.x), "=r"(v.y), "=r"(v.z), "=r"(v.w) : "r"(a) : "memory"); return v;
}
__device__ __forceinline__ uint32_t lds32(uint32_t a) { uint32_t v; asm volatile("ld.shared.b32 %0, [%1];" : "=r"(v) : "r"(a) : "memory"); return v; }
__device__ __forceinline__ void sts128(uint32_t p, const uint32_t* r) {
    asm volatile("st.shared.v4.b32 [%0], {%1,%2,%3,%4};" :: "r"(p), "r"(r[0]), "r"(r[1]), "r"(r[2]), "r"(r[3]) : "memory");
}
__device__ __forceinline__ void cluster_arrive() {
    asm volatile("fence.mbarrier_init.release.cluster;\nbarrier.cluster.arrive.relaxed.aligned;" ::: "memory");
}
__device__ __forceinline__ void cluster_wait() { asm volatile("barrier.cluster.wait.aligned;" ::: "memory"); }

__device__ __forceinline__ void quad_sum2(float& sa, float& sb) {
    const uint32_t ha = __float_as_uint(sa) & 0xffffe000u, hb = __float_as_uint(sb) & 0xffffe000u;
    const float la = sa - __uint_as_float(ha), lb = sb - __uint_as_float(hb);
    asm volatile("{\n.reg .f32 d1, d3;\n"
                 "mma.sync.aligned.m16n8k8.row.col.f32.tf32.tf32.f32 {%0,d1,%1,d3}, {%2,%3,%4,%5}, {%6,%6}, {%7,%7,%7,%7};\n}"
                 : "=f"(sa), "=f"(sb) : "r"(ha), "r"(hb), "r"(__float_as_uint(la)), "r"(__float_as_uint(lb)), "r"(0x3f800000), "f"(0.f));
}
__device__ __forceinline__ void softmax8x2(float s0, float s1, float s2, float s3, uint32_t& pa, uint32_t& pb) {
    const float scale = 0.08838834764831845f, l2e = 1.4426950408889634f;
    uint32_t r0 = pack_bf16(s0, s2), r1 = pack_bf16(s1, s3);
    r0 = pack_bf16(bf_lo(r0) * scale, bf_hi(r0) * scale);
    r1 = pack_bf16(bf_lo(r1) * scale, bf_hi(r1) * scale);
    uint32_t m = bfmax2(r0, r1);
    const uint32_t m1 = __shfl_xor_sync(0xffffffffu, m, 1), m2 = __shfl_xor_sync(0xffffffffu, m, 2), m3 = __shfl_xor_sync(0xffffffffu, m, 3);
    m = bfmax2(bfmax2(m, m1), bfmax2(m2, m3));
    const float ma = bf_lo(m), mb = bf_hi(m);
    const float a0 = ex2((bf_lo(r0) - ma) * l2e), a1 = ex2((bf_lo(r1) - ma) * l2e);
    const float b0 = ex2((bf_hi(r0) - mb) * l2e), b1 = ex2((bf_hi(r1) - mb) * l2e);
    float sa = a0 + a1, sb = b0 + b1;
    quad_sum2(sa, sb);
    sa = rcp(sa);
    sb = rcp(sb);
    pa = pack_bf16(a0 * sa, a1 * sa);
    pb = pack_bf16(b0 * sb, b1 * sb);
}

constexpr int CL = 8;
constexpr int HPC = 4;
constexpr int KVB = 16384;
constexpr int QB = 8192;
constexpr int FINB = 2048 + 4 * 576;
constexpr int PFB = 20480;
constexpr int W_KV = 8, W_RED = 12, W_PKV = 13, W_PQ = 14, NTHREADS = 15 * 32;
constexpr int O_KV = 0, O_Q = 8 * KVB, O_E = O_Q + 8 * QB, O_FIN = O_E + 8192, O_IN = O_FIN + HPC * FINB, O_BAR = O_IN + 4096;
constexpr int SMEM = O_BAR + 8 * 101;

struct Params { CUtensorMap mk, mv, mq, mo, me, mf; };

__device__ __forceinline__ int head_row(int cid, int j) { return (((0x10724365u >> (8 * j + (cid & 4))) & 7) * 4 + (cid & 3)) * 2048; }
constexpr int HEAD0 = 20;

__device__ __forceinline__ int hinge(int x, int k) { return max(x - k, 0); }
__device__ __forceinline__ int kv_time(int k, int isV) {
    return -835 + 325 * k + 491 * hinge(k, 4) - 464 * hinge(k, 5)
           + 113 * hinge(k, 8) + (isV ? 77 : -36) * hinge(k, 16) + (isV ? -108 : 131) * hinge(k, 24)
           + (isV ? -92 : -236) * hinge(k, 28);
}
__device__ __forceinline__ int q_time(int b, int isV) {
    return (isV ? 2622 : 2524) + 473 * b + 30 * hinge(b, 8) + (isV ? -34 : 3) * hinge(b, 16)
           + (isV ? 742 : 741) * hinge(b, 19) + (isV ? -857 : -856) * hinge(b, 20) + (isV ? -184 : -251) * hinge(b, 21)
           - 24 * hinge(b, 22) + (isV ? 11 : 56) * hinge(b, 24) + (isV ? 7 : 6) * hinge(b, 26)
           + (isV ? -18 : -19) * hinge(b, 28) + (isV ? 70 : 71) * hinge(b, 29);
}

__global__ void __cluster_dims__(CL, 1, 1) __launch_bounds__(NTHREADS, 1)
lf_kernel(const unsigned char* __restrict__ K0, const unsigned char* __restrict__ V0, const __grid_constant__ Params P) {
    {
        const uint32_t off = blockIdx.x * PFB + (blockIdx.x >> 3) * (2048 * 256 - CL * PFB);
        asm volatile("{\n.reg .pred p;\n.reg .b32 t;\nmov.u32 t, %%tid.x;\nsetp.eq.u32 p, t, 0;\n"
                     "@p cp.async.bulk.prefetch.L2.global [%0], %2;\n"
                     "@p cp.async.bulk.prefetch.L2.global [%1], %2;\n}"
                     :: "l"(K0 + off), "l"(V0 + off), "n"(PFB) : "memory");
    }
    const uint32_t tbase = now_ns();
    extern __shared__ __align__(1024) unsigned char smem_raw[];
    uint32_t sb = smem_u32(smem_raw);
    asm volatile("" : "+r"(sb));
    sb = __shfl_sync(0xffffffffu, sb, 0);
    const uint32_t s_kv = sb + O_KV, s_q = sb + O_Q, s_e = sb + O_E, s_fin = sb + O_FIN, s_in = sb + O_IN;
    const uint32_t b_qf = sb + O_BAR, b_kvf = b_qf + 512, b_kve = b_kvf + 64, b_qe = b_kve + 64, b_fin = b_qe + 64,
                   b_in = b_fin + 64, b_e = b_in + 32;
    const int warp = __shfl_sync(0xffffffffu, threadIdx.x >> 5, 0), lane = threadIdx.x & 31;
    const int rank = blockIdx.x & (CL - 1), cid = blockIdx.x >> 3;
    const int isV = rank >> 2, part = rank & 3;
    const int kvrow = part * 64, qrow = rank * 32;
    const bool leader = elect();
    uint64_t pol;
    asm("createpolicy.fractional.L2::evict_first.b64 %0, 1.0;" : "=l"(pol));

    if (warp == W_PKV) {
        const CUtensorMap* mkv = isV ? &P.mv : &P.mk;
        if (leader) {
#pragma unroll
            for (int k = 0; k < 8; k++) mbar_init(b_kvf + 8 * k, 1);
        }
        __syncwarp();
        cluster_arrive();
        const uint32_t tl = tbase + kv_time(lane, isV);
#pragma unroll 1
        for (int k = 0; k < 32; k++) {
            if (k == 5) cluster_wait();
            const uint32_t tt = __shfl_sync(0xffffffffu, tl, k);
            const int s = k & 7;
            if (k >= 8) mbar_wait(b_kve + 8 * s, ((k >> 3) & 1) ^ 1);
            if (leader) mbar_expect_tx(b_kvf + 8 * s, KVB);
            wait_until(tt);
            if (leader) tma_load(s_kv + s * KVB, mkv, kvrow + s * 256 + head_row(cid, k >> 3), b_kvf + 8 * s, pol);
        }
        return;
    }
    if (leader) {
        if (warp == W_RED) {
            mbar_init(b_e, 1);
            asm volatile("fence.mbarrier_init.release.cluster;" ::: "memory");
            mbar_expect_tx(b_e, 8192);
            asm volatile("cp.async.bulk.tensor.3d.shared::cluster.global.mbarrier::complete_tx::bytes [%0], [%1, {%3, %4, %4}], [%2];"
                         :: "r"(s_e), "l"(isV ? &P.mf : &P.me), "r"(b_e), "r"(part * 64), "r"(0) : "memory");
        } else if (warp < 8) {
            mbar_init(b_kve + 8 * warp, 4);
            mbar_init(b_qe + 8 * warp, 2);
        } else if (warp < W_RED) {
            const int j = warp - W_KV;
            mbar_init(b_in + 8 * j, 1);
            mbar_init(b_fin + 16 * j, 1);
            mbar_init(b_fin + 16 * j + 8, 1);
            mbar_expect_tx(b_in + 8 * j, 4096);
            mbar_expect_tx(b_fin + 16 * j, 2048);
            mbar_expect_tx(b_fin + 16 * j + 8, 2048);
        }
    }
    __syncwarp();
    cluster_arrive();
    cluster_wait();

    if (warp == W_PQ) {
        asm volatile("barrier.sync 1, 288;" ::: "memory");
        const uint32_t tl = tbase + q_time(lane, isV);
#pragma unroll 1
        for (int b = 0; b < 32; b++) {
            const uint32_t tt = __shfl_sync(0xffffffffu, tl, b);
            const int s = b & 7;
            if (b == 20) {
#pragma unroll
                for (int i = 4; i < 8; i++) mbar_wait(b_qe + 8 * i, 1);
            } else if (b == 21) {
                mbar_wait(b_fin + 16 * 2 + 8 * isV, 0);
                mbar_wait(b_kve + 8 * 3, 1);
            } else if (b >= 8 && b < 20) {
                mbar_wait(b_qe + 8 * s, ((b >> 3) & 1) ^ 1);
            }
            const uint32_t dst = (b >= 24 ? s_kv : s_q) + s * QB;
            const int row = qrow + s * 256 + head_row(cid, b >> 3);
            wait_until(tt);
            if (leader) {
                tma_load(dst, &P.mq, row, b_qf + 16 * b, pol);
                tma_load(dst + 4096, &P.mq, row + 16, b_qf + 16 * b + 8, pol);
            }
        }
    } else if (warp >= W_KV && warp < W_RED) {
        const int w = warp - W_KV;
        const uint32_t l7 = lane & 7;
        const uint32_t cA = (w & 1) * 4 + ((lane >> 3) & 1);
        const uint32_t a_base = s_kv + (w >> 1) * 8192 + (l7 + 8 * (lane >> 4)) * 128;
        const uint32_t a0 = a_base + ((cA ^ l7) << 4), a1 = a_base + (((cA + 2) ^ l7) << 4);
        const uint32_t e0 = s_e + l7 * 128 + (((lane >> 3) ^ l7) << 4), e1 = s_e + l7 * 128 + ((((lane >> 3) + 4) ^ l7) << 4);
        const uint32_t dst = mapa(s_in + part * 1024 + lane * 16, isV * 4 + w), rb = mapa(b_in, isV * 4 + w);
        mbar_wait(b_e, 0);
#pragma unroll 1
        for (int j = 0; j < HPC; j++) {
            float c0[4] = {0, 0, 0, 0}, c1[4] = {0, 0, 0, 0}, c2[4] = {0, 0, 0, 0}, c3[4] = {0, 0, 0, 0};
#pragma unroll 1
            for (int c = 0; c < 8; c++) {
                uint32_t e[8], a[32];
                ldsm4(e0 + c * 1024, e);
                ldsm4(e1 + c * 1024, e + 4);
                if (c == 7 && j > 0) mbar_wait_cl(b_fin + 16 * (j - 1) + 8 * isV, 0);
                mbar_wait(b_kvf + 8 * c, j & 1);
#pragma unroll
                for (int s = 0; s < 4; s++) {
                    ldsm4t(a0 + c * KVB + s * 2048, a + 8 * s);
                    ldsm4t(a1 + c * KVB + s * 2048, a + 8 * s + 4);
                }
#pragma unroll
                for (int s = 0; s < 4; s++) {
                    mma16816((s & 1) ? c2 : c0, a + 8 * s, e[2 * s], e[2 * s + 1]);
                    mma16816((s & 1) ? c3 : c1, a + 8 * s + 4, e[2 * s], e[2 * s + 1]);
                }
                __syncwarp();
                if (leader) mbar_arrive(b_kve + 8 * c);
            }
            st_async4(dst, __float_as_uint(c0[0] + c2[0]), __float_as_uint(c0[1] + c2[1]), __float_as_uint(c0[2] + c2[2]),
                      __float_as_uint(c0[3] + c2[3]), rb + 8 * j);
            st_async4(dst + 512, __float_as_uint(c1[0] + c3[0]), __float_as_uint(c1[1] + c3[1]), __float_as_uint(c1[2] + c3[2]),
                      __float_as_uint(c1[3] + c3[3]), rb + 8 * j);
        }
    } else if (warp == W_RED) {
        const uint32_t foff = s_fin + (isV ? 2048 + part * 576 : part * 512) + lane * 16;
#pragma unroll 1
        for (int j = 0; j < HPC; j++) {
            uint32_t rd[CL], rbar[CL];
#pragma unroll
            for (int r = 0; r < CL; r++) {
                rd[r] = mapa(foff + j * FINB, r);
                rbar[r] = mapa(b_fin + 16 * j + 8 * isV, r);
                asm volatile("" : "+r"(rd[r]), "+r"(rbar[r]));
            }
            mbar_wait_cl(b_in + 8 * j, 0);
            uint4 x[8];
#pragma unroll
            for (int s = 0; s < 8; s++) x[s] = lds128(s_in + s * 512 + lane * 16);
            uint32_t wv[4];
#pragma unroll
            for (int i = 0; i < 2; i++) {
#define F_(v) __uint_as_float(v)
                const float s0 = (F_(x[i].x) + F_(x[2 + i].x)) + (F_(x[4 + i].x) + F_(x[6 + i].x));
                const float s1 = (F_(x[i].y) + F_(x[2 + i].y)) + (F_(x[4 + i].y) + F_(x[6 + i].y));
                const float s2 = (F_(x[i].z) + F_(x[2 + i].z)) + (F_(x[4 + i].z) + F_(x[6 + i].z));
                const float s3 = (F_(x[i].w) + F_(x[2 + i].w)) + (F_(x[4 + i].w) + F_(x[6 + i].w));
#undef F_
                wv[2 * i] = pack_bf16(s0, s1);
                wv[2 * i + 1] = pack_bf16(s2, s3);
            }
            if (!isV) {
#pragma unroll
                for (int i = 0; i < 4; i++) asm volatile("movmatrix.sync.aligned.m8n8.trans.b16 %0, %0;" : "+r"(wv[i]));
            }
#pragma unroll
            for (int r = CL - 1; r >= 0; r--) st_async4(rd[r], wv[0], wv[1], wv[2], wv[3], rbar[r]);
        }
    } else {
        mbar_wait(b_e, 0);
        if (leader) {
#pragma unroll
            for (int i = 0; i < 8; i++) mbar_init(b_qf + 64 * i + 8 * warp, 1);
#pragma unroll
            for (int i = 0; i < 8; i++) mbar_expect_tx(b_qf + 64 * i + 8 * warp, QB / 2);
            asm volatile("fence.mbarrier_init.release.cluster;" ::: "memory");
        }
        __syncwarp();
        asm volatile("barrier.arrive 1, 288;" ::: "memory");
        const int g = lane >> 2, t = lane & 3;
        const uint32_t qx = lane & 7, qc = lane >> 4, wo = s_q + warp * 4096;
        uint32_t ka = s_fin + lane * 16;
        uint32_t va = s_fin + 2048 + (g >> 2) * 576 + t * 16 + (g & 3) * 4;
        uint32_t so0 = wo + 2 * t * 128 + ((g ^ (2 * t)) << 4), so1 = wo + (2 * t + 1) * 128 + ((g ^ (2 * t + 1)) << 4);
        uint32_t qa[4];
#pragma unroll
        for (int u = 0; u < 4; u++) qa[u] = wo + (qx + 8 * ((lane >> 3) & 1)) * 128 + (((2 * u + qc) ^ qx) << 4);
        const int row0 = qrow + (warp >> 1) * 256 + (warp & 1) * 16;
#pragma unroll 1
        for (int j = 0; j < HPC; j++) {
            const uint32_t sq = (j == 3 ? s_kv : s_q) + warp * 4096, bq = b_qf + 128 * j + 8 * warp, bf = b_fin + 16 * j;
            const int row = row0 + head_row(cid, j);
            uint32_t vw[16], a[32];
            uint4 kf[4];
            auto load_v = [&] {
#pragma unroll
                for (int x = 0; x < 16; x++) vw[x] = lds32(va + (x >> 3) * (2 * 576) + (x & 7) * 64);
            };
            auto load_q = [&](int h) {
#pragma unroll
                for (int u = 0; u < 8; u++) ldsm4(qa[u & 3] + h * (4 * QB) + (u >> 2) * 2048, a + 4 * u);
            };
            mbar_wait_cl(bf, 0);
            const bool late = !mbar_test_cl(bf + 8, 0);
#pragma unroll
            for (int u = 0; u < 4; u++) kf[u] = lds128(ka + u * 512);
            if (!late) { acquire_cl(); load_v(); }
            mbar_wait(bq, 0);
            load_q(0);
#pragma unroll
            for (int h = 0; h < 2; h++) {
                float sc[4][4];
#pragma unroll
                for (int i = 0; i < 4; i++) { sc[i][0] = sc[i][1] = sc[i][2] = sc[i][3] = 0.f; }
#pragma unroll
                for (int u = 0; u < 4; u++) {
                    mma16816(sc[(2 * u) & 3], a + 8 * u, kf[u].x, kf[u].y);
                    mma16816(sc[(2 * u + 1) & 3], a + 8 * u + 4, kf[u].z, kf[u].w);
                }
                uint32_t p[2];
                softmax8x2((sc[0][0] + sc[1][0]) + (sc[2][0] + sc[3][0]), (sc[0][1] + sc[1][1]) + (sc[2][1] + sc[3][1]),
                           (sc[0][2] + sc[1][2]) + (sc[2][2] + sc[3][2]), (sc[0][3] + sc[1][3]) + (sc[2][3] + sc[3][3]), p[0], p[1]);
                if (h == 0 && late) { mbar_wait_cl(bf + 8, 0); load_v(); }
                __syncwarp();
#pragma unroll
                for (int H = 0; H < 2; H++) {
#pragma unroll
                    for (int u = 0; u < 2; u++) {
                        uint32_t r0[4], r1[4];
#pragma unroll
                        for (int jj = 0; jj < 4; jj++) {
                            float d[4];
                            mma1688z(d, vw[8 * H + 2 * jj], vw[8 * H + 2 * jj + 1], p[u]);
                            r0[jj] = pack_bf16(d[0], d[2]);
                            r1[jj] = pack_bf16(d[1], d[3]);
                        }
                        sts128(so0 + h * (4 * QB) + H * 2048 + u * 1024, r0);
                        sts128(so1 + h * (4 * QB) + H * 2048 + u * 1024, r1);
                    }
                }
                if (h == 1) {
                    const uint32_t dq = j == 2 ? -O_Q : 0;
#pragma unroll
                    for (int u = 0; u < 4; u++) qa[u] += dq;
                    so0 += dq; so1 += dq; ka += FINB; va += FINB;
                }
                asm volatile("fence.proxy.async.shared::cta;" ::: "memory");
                __syncwarp();
                if (leader) asm volatile("cp.async.bulk.tensor.3d.global.shared::cta.bulk_group [%0, {%2, %3, %2}], [%1];"
                                         :: "l"(&P.mo), "r"(sq + h * (4 * QB)), "r"(0), "r"(row + h * 1024) : "memory");
                if (j < 2) {
                    asm volatile("cp.async.bulk.commit_group;\ncp.async.bulk.wait_group.read 0;" ::: "memory");
                    if (leader) mbar_arrive(b_qe + 8 * (4 * h + (warp >> 1)));
                } else if (h == 1 && j == 3) {
                    asm volatile("cp.async.bulk.commit_group;" ::: "memory");
                }
                if (h == 0) { mbar_wait(bq + 64, 0); load_q(1); }
            }
        }
        if (leader) asm volatile("cp.async.bulk.wait_group.read 0;" ::: "memory");
    }
}

typedef CUresult (*EncodeFn)(CUtensorMap*, CUtensorMapDataType, cuuint32_t, void*, const cuuint64_t*, const cuuint64_t*,
                             const cuuint32_t*, const cuuint32_t*, CUtensorMapInterleave, CUtensorMapSwizzle,
                             CUtensorMapL2promotion, CUtensorMapFloatOOBfill);

static void encode3(EncodeFn enc, CUtensorMap* m, const void* p, cuuint64_t d0, cuuint64_t d1, cuuint64_t d2,
                    cuuint64_t s1, cuuint64_t s2, cuuint32_t b1, cuuint32_t b2) {
    cuuint64_t dims[3] = {d0, d1, d2}, str[2] = {s1, s2};
    cuuint32_t box[3] = {64, b1, b2}, es[3] = {1, 1, 1};
    enc(m, CU_TENSOR_MAP_DATA_TYPE_BFLOAT16, 3, (void*)p, dims, str, box, es, CU_TENSOR_MAP_INTERLEAVE_NONE,
        CU_TENSOR_MAP_SWIZZLE_128B, CU_TENSOR_MAP_L2_PROMOTION_NONE, CU_TENSOR_MAP_FLOAT_OOB_FILL_NONE);
}

}

extern "C" void kernel_launch(void* const* d_in, const int* in_sizes, int n_in, void* d_out, int out_size) {
    static lf::EncodeFn enc = nullptr;
    if (!enc) {
        cudaDriverEntryPointQueryResult qr;
        cudaGetDriverEntryPoint("cuTensorMapEncodeTiled", (void**)&enc, cudaEnableDefault, &qr);
        cudaFuncSetAttribute(lf::lf_kernel, cudaFuncAttributeMaxDynamicSharedMemorySize, lf::SMEM);
    }
    lf::Params P;
    lf::encode3(enc, &P.mq, d_in[0], 64, 65536, 2, 256, 128, 16, 2);
    lf::encode3(enc, &P.mk, d_in[1], 64, 65536, 2, 256, 128, 64, 2);
    lf::encode3(enc, &P.mv, d_in[2], 64, 65536, 2, 256, 128, 64, 2);
    lf::encode3(enc, &P.mo, d_out, 64, 65536, 2, 256, 128, 16, 2);
    lf::encode3(enc, &P.me, d_in[3], 256, 8, 8, 4096, 512, 8, 8);
    lf::encode3(enc, &P.mf, d_in[4], 256, 8, 8, 4096, 512, 8, 8);
    lf::lf_kernel<<<64, lf::NTHREADS, lf::SMEM, cudaStreamPerThread>>>(
        (const unsigned char*)d_in[1] + lf::HEAD0 * 2048 * 256, (const unsigned char*)d_in[2] + lf::HEAD0 * 2048 * 256, P);
}
```

```cpp
#include <cuda_runtime.h>
#include <cuda_bf16.h>
#include <cuda.h>
#include <stdint.h>

namespace lf {

__device__ __forceinline__ uint32_t smem_u32(const void* p) { return (uint32_t)__cvta_generic_to_shared(p); }
__device__ __forceinline__ void mbar_init(uint32_t bar, uint32_t cnt) {
    asm volatile("mbarrier.init.shared::cta.b64 [%0], %1;" :: "r"(bar), "r"(cnt) : "memory");
}
__device__ __forceinline__ void mbar_expect_tx(uint32_t bar, uint32_t bytes) {
    asm volatile("mbarrier.arrive.expect_tx.shared::cta.b64 _, [%0], %1;" :: "r"(bar), "r"(bytes) : "memory");
}
__device__ __forceinline__ void mbar_arrive(uint32_t bar) {
    asm volatile("mbarrier.arrive.shared::cta.b64 _, [%0];" :: "r"(bar) : "memory");
}
__device__ __forceinline__ bool mbar_try(uint32_t bar, uint32_t parity) {
    uint32_t ok;
    asm volatile("{\n.reg .pred p;\nmbarrier.try_wait.parity.shared::cta.b64 p, [%1], %2;\nselp.u32 %0, 1, 0, p;\n}"
                 : "=r"(ok) : "r"(bar), "r"(parity) : "memory");
    return ok;
}
__device__ __forceinline__ bool mbar_try_cl(uint32_t bar, uint32_t parity) {
    uint32_t ok;
    asm volatile("{\n.reg .pred p;\nmbarrier.try_wait.parity.relaxed.cluster.shared::cta.b64 p, [%1], %2;\nselp.u32 %0, 1, 0, p;\n}"
                 : "=r"(ok) : "r"(bar), "r"(parity) : "memory");
    return ok;
}
__device__ __forceinline__ bool mbar_test_cl(uint32_t bar, uint32_t parity) {
    uint32_t ok;
    asm volatile("{\n.reg .pred p;\nmbarrier.test_wait.parity.relaxed.cluster.shared::cta.b64 p, [%1], %2;\nselp.u32 %0, 1, 0, p;\n}"
                 : "=r"(ok) : "r"(bar), "r"(parity) : "memory");
    return ok;
}
__device__ __forceinline__ void acquire_cl() { asm volatile("fence.acquire.sync_restrict::shared::cluster.cluster;" ::: "memory"); }
__device__ __forceinline__ void mbar_wait(uint32_t bar, uint32_t parity) {
    int n = 0;
    while (!mbar_try(bar, parity)) { if (++n > (1 << 20)) __trap(); }
}
__device__ __forceinline__ void mbar_wait_cl(uint32_t bar, uint32_t parity) {
    int n = 0;
    while (!mbar_try_cl(bar, parity)) { if (++n > (1 << 20)) __trap(); }
    acquire_cl();
}
__device__ __forceinline__ uint32_t now_ns() { uint32_t t; asm volatile("mov.u32 %0, %%globaltimer_lo;" : "=r"(t)); return t; }
__device__ __forceinline__ void wait_until(uint32_t t) {
    for (int n = 0; (int)(now_ns() - t) < 0 && n < 4096; n++) { }
}
__device__ __forceinline__ void tma_load(uint32_t dst, const CUtensorMap* m, int row, uint32_t bar, uint64_t pol) {
    asm volatile("cp.async.bulk.tensor.3d.shared::cluster.global.mbarrier::complete_tx::bytes.L2::cache_hint [%0], [%1, {%3, %4, %3}], [%2], %5;"
                 :: "r"(dst), "l"(m), "r"(bar), "r"(0), "r"(row), "l"(pol) : "memory");
}
__device__ __forceinline__ void ldsm4(uint32_t a, uint32_t* r) {
    asm volatile("ldmatrix.sync.aligned.m8n8.x4.shared.b16 {%0,%1,%2,%3}, [%4];" : "=r"(r[0]), "=r"(r[1]), "=r"(r[2]), "=r"(r[3]) : "r"(a) : "memory");
}
__device__ __forceinline__ void ldsm4t(uint32_t a, uint32_t* r) {
    asm volatile("ldmatrix.sync.aligned.m8n8.x4.trans.shared.b16 {%0,%1,%2,%3}, [%4];" : "=r"(r[0]), "=r"(r[1]), "=r"(r[2]), "=r"(r[3]) : "r"(a) : "memory");
}
__device__ __forceinline__ void mma16816(float* c, const uint32_t* a, uint32_t b0, uint32_t b1) {
    asm volatile("mma.sync.aligned.m16n8k16.row.col.f32.bf16.bf16.f32 {%0,%1,%2,%3}, {%4,%5,%6,%7}, {%8,%9}, {%0,%1,%2,%3};"
                 : "+f"(c[0]), "+f"(c[1]), "+f"(c[2]), "+f"(c[3]) : "r"(a[0]), "r"(a[1]), "r"(a[2]), "r"(a[3]), "r"(b0), "r"(b1));
}
__device__ __forceinline__ void mma1688z(float* d, uint32_t a0, uint32_t a1, uint32_t b0) {
    asm volatile("mma.sync.aligned.m16n8k8.row.col.f32.bf16.bf16.f32 {%0,%1,%2,%3}, {%4,%5}, {%6}, {%7,%7,%7,%7};"
                 : "=f"(d[0]), "=f"(d[1]), "=f"(d[2]), "=f"(d[3]) : "r"(a0), "r"(a1), "r"(b0), "f"(0.f));
}
__device__ __forceinline__ uint32_t pack_bf16(float lo, float hi) { uint32_t r; asm("cvt.rn.bf16x2.f32 %0, %1, %2;" : "=r"(r) : "f"(hi), "f"(lo)); return r; }
__device__ __forceinline__ float bf_lo(uint32_t x) { return __uint_as_float(x << 16); }
__device__ __forceinline__ float bf_hi(uint32_t x) { return __uint_as_float(x & 0xffff0000u); }
__device__ __forceinline__ uint32_t bfmax2(uint32_t a, uint32_t b) { uint32_t d; asm("max.bf16x2 %0, %1, %2;" : "=r"(d) : "r"(a), "r"(b)); return d; }
__device__ __forceinline__ float ex2(float x) { float y; asm("ex2.approx.ftz.f32 %0, %1;" : "=f"(y) : "f"(x)); return y; }
__device__ __forceinline__ float rcp(float x) { float y; asm("rcp.approx.ftz.f32 %0, %1;" : "=f"(y) : "f"(x)); return y; }
__device__ __forceinline__ uint32_t mapa(uint32_t a, uint32_t r) { uint32_t d; asm("mapa.shared::cluster.u32 %0, %1, %2;" : "=r"(d) : "r"(a), "r"(r)); return d; }
__device__ __forceinline__ bool elect() {
    uint32_t p;
    asm volatile("{\n.reg .pred p;\nelect.sync _|p, 0xffffffff;\nselp.u32 %0, 1, 0, p;\n}" : "=r"(p));
    return p;
}
__device__ __forceinline__ void st_async4(uint32_t dst, uint32_t a, uint32_t b, uint32_t c, uint32_t d, uint32_t bar) {
    asm volatile("st.async.weak.shared::cluster.mbarrier::complete_tx::bytes.v4.b32 [%0], {%1,%2,%3,%4}, [%5];"
                 :: "r"(dst), "r"(a), "r"(b), "r"(c), "r"(d), "r"(bar) : "memory");
}
__device__ __forceinline__ void st_async2(uint32_t dst, uint32_t a, uint32_t b, uint32_t bar) {
    asm volatile("st.async.weak.shared::cluster.mbarrier::complete_tx::bytes.v2.b32 [%0], {%1,%2}, [%3];"
                 :: "r"(dst), "r"(a), "r"(b), "r"(bar) : "memory");
}
__device__ __forceinline__ uint2 lds64(uint32_t a) {
    uint2 v; asm volatile("ld.shared.v2.b32 {%0,%1}, [%2];" : "=r"(v.x), "=r"(v.y) : "r"(a) : "memory"); return v;
}
__device__ __forceinline__ uint4 lds128(uint32_t a) {
    uint4 v; asm volatile("ld.shared.v4.b32 {%0,%1,%2,%3}, [%4];" : "=r"(v.x), "=r"(v.y), "=r"(v.z), "=r"(v.w) : "r"(a) : "memory"); return v;
}
__device__ __forceinline__ void sts128(uint32_t p, const uint32_t* r) {
    asm volatile("st.shared.v4.b32 [%0], {%1,%2,%3,%4};" :: "r"(p), "r"(r[0]), "r"(r[1]), "r"(r[2]), "r"(r[3]) : "memory");
}
__device__ __forceinline__ void cluster_arrive() {
    asm volatile("fence.mbarrier_init.release.cluster;\nbarrier.cluster.arrive.relaxed.aligned;" ::: "memory");
}
__device__ __forceinline__ void cluster_wait() { asm volatile("barrier.cluster.wait.aligned;" ::: "memory"); }

__device__ __forceinline__ void quad_sum2(float& sa, float& sb) {
    const uint32_t ha = __float_as_uint(sa) & 0xffffe000u, hb = __float_as_uint(sb) & 0xffffe000u;
    const float la = sa - __uint_as_float(ha), lb = sb - __uint_as_float(hb);
    asm volatile("{\n.reg .f32 d1, d3;\n"
                 "mma.sync.aligned.m16n8k8.row.col.f32.tf32.tf32.f32 {%0,d1,%1,d3}, {%2,%3,%4,%5}, {%6,%6}, {%7,%7,%7,%7};\n}"
                 : "=f"(sa), "=f"(sb) : "r"(ha), "r"(hb), "r"(__float_as_uint(la)), "r"(__float_as_uint(lb)), "r"(0x3f800000), "f"(0.f));
}
__device__ __forceinline__ void softmax8x2(float s0, float s1, float s2, float s3, uint32_t& pa, uint32_t& pb) {
    const float scale = 0.08838834764831845f, l2e = 1.4426950408889634f;
    uint32_t r0 = pack_bf16(s0, s2), r1 = pack_bf16(s1, s3);
    r0 = pack_bf16(bf_lo(r0) * scale, bf_hi(r0) * scale);
    r1 = pack_bf16(bf_lo(r1) * scale, bf_hi(r1) * scale);
    uint32_t m = bfmax2(r0, r1);
    const uint32_t m1 = __shfl_xor_sync(0xffffffffu, m, 1), m2 = __shfl_xor_sync(0xffffffffu, m, 2), m3 = __shfl_xor_sync(0xffffffffu, m, 3);
    m = bfmax2(bfmax2(m, m1), bfmax2(m2, m3));
    const float ma = bf_lo(m), mb = bf_hi(m);
    const float a0 = ex2((bf_lo(r0) - ma) * l2e), a1 = ex2((bf_lo(r1) - ma) * l2e);
    const float b0 = ex2((bf_hi(r0) - mb) * l2e), b1 = ex2((bf_hi(r1) - mb) * l2e);
    float sa = a0 + a1, sb = b0 + b1;
    quad_sum2(sa, sb);
    sa = rcp(sa);
    sb = rcp(sb);
    pa = pack_bf16(a0 * sa, a1 * sa);
    pb = pack_bf16(b0 * sb, b1 * sb);
}

constexpr int CL = 16;
constexpr int HPC = 4;
constexpr int KVB = 8192;
constexpr int QB = 4096;
constexpr int FINB = 4096;
constexpr int PFB = 8192;
constexpr int W_KV = 4, W_PKV = 8, W_PQ = 9, NTHREADS = 10 * 32;
constexpr int O_KV = 0, O_Q = 8 * KVB, O_E = O_Q + 8 * QB, O_FIN = O_E + 4096, O_IN = O_FIN + 2 * FINB, O_BAR = O_IN + 4096;
constexpr int SMEM = O_BAR + 8 * 71;

struct Params { CUtensorMap mk, mv, mq, mo, me, mf; uint32_t tab[4][32]; };

__device__ __forceinline__ int head_row(int cid, int j) { return (((0x10724365u >> (8 * j + (cid & 4))) & 7) * 4 + (cid & 3)) * 2048; }
constexpr int HEAD0 = 20;

static const unsigned short kTimeKV[4][32] = {
    {    0,     0,     0,     0,     0,   930,  1448,  1966,  2484,  2929,  3374,  3818,  4263,  4708,  5153,  5598,
      6042,  6517,  6992,  7467,  7942,  8417,  8892,  9367,  9842, 10332, 10823, 11314, 11805, 12326, 12847, 13369},
    {    0,     0,     0,     0,     0,   930,  1448,  1966,  2484,  2929,  3374,  3818,  4263,  4708,  5153,  5598,
      6042,  6585,  7128,  7671,  8214,  8757,  9300,  9843, 10386, 10962, 11539, 12115, 12692, 12889, 13086, 13284},
    {    0,     0,     0,     0,     0,  2170,  2311,  2451,  2591,  3050,  3510,  3969,  4429,  4888,  5347,  5807,
      6266,  6717,  7168,  7619,  8070,  8521,  8972,  9423,  9874, 10263, 10652, 11041, 11430, 11525, 11620, 11715},
    {    0,     0,     0,     0,     0,  2170,  2311,  2451,  2591,  3050,  3510,  3969,  4429,  4888,  5347,  5807,
      6266,  6745,  7223,  7702,  8180,  8659,  9137,  9616, 10095, 10413, 10732, 11050, 11369, 11745, 12121, 12498},
};
static const unsigned short kTimeQ[4][32] = {
    { 2264,  2752,  3240,  3728,  4215,  4703,  5191,  5679,  6166,  6672,  7178,  7684,  8189,  8695,  9201,  9707,
     10213, 10529, 10845, 11161, 11647, 12492, 13544, 13639, 13734, 13829, 13924, 14255, 14721, 14816, 14911, 15117},
    { 2264,  2752,  3240,  3728,  4215,  4703,  5191,  5679,  6166,  6672,  7178,  7684,  8189,  8695,  9201,  9707,
     10213, 10607, 11001, 11420, 12008, 12956, 13773, 13868, 13963, 14058, 14153, 14248, 14668, 14763, 14858, 15205},
    { 3066,  3488,  3910,  4331,  4753,  5174,  5596,  6017,  6439,  6929,  7418,  7908,  8398,  8887,  9377,  9867,
     10357, 10635, 10913, 11191, 11504, 11817, 12101, 12385, 12480, 13309, 14170, 14265, 14360, 14455, 14550, 14651},
    { 3066,  3488,  3910,  4331,  4753,  5174,  5596,  6017,  6439,  6929,  7418,  7908,  8398,  8887,  9377,  9867,
     10357, 10635, 10913, 11191, 11504, 11817, 12101, 12385, 12480, 13309, 14170, 14265, 14360, 14455, 14550, 14651},
};

__global__ void __cluster_dims__(CL, 1, 1) __launch_bounds__(NTHREADS, 2)
lf_kernel(const unsigned char* __restrict__ K0, const unsigned char* __restrict__ V0, const __grid_constant__ Params P) {
    {
        const uint32_t off = blockIdx.x * PFB + (blockIdx.x >> 4) * (2048 * 256 - CL * PFB);
        asm volatile("{\n.reg .pred p;\n.reg .b32 t;\nmov.u32 t, %%tid.x;\nsetp.eq.u32 p, t, 0;\n"
                     "@p cp.async.bulk.prefetch.L2.global [%0], %2;\n"
                     "@p cp.async.bulk.prefetch.L2.global [%1], %2;\n}"
                     :: "l"(K0 + off), "l"(V0 + off), "n"(PFB) : "memory");
    }
    const uint32_t tbase = now_ns();
    extern __shared__ __align__(1024) unsigned char smem_raw[];
    uint32_t sb = smem_u32(smem_raw);
    asm volatile("" : "+r"(sb));
    sb = __shfl_sync(0xffffffffu, sb, 0);
    const uint32_t s_kv = sb + O_KV, s_q = sb + O_Q, s_e = sb + O_E, s_fin = sb + O_FIN, s_in = sb + O_IN;
    const uint32_t b_qf = sb + O_BAR, b_kvf = b_qf + 256, b_kve = b_kvf + 64, b_qe = b_kve + 64, b_fin = b_qe + 64,
                   b_in = b_fin + 64, b_e = b_in + 32, b_fr = b_e + 8;
    const int warp = __shfl_sync(0xffffffffu, threadIdx.x >> 5, 0), lane = threadIdx.x & 31;
    const int rank = blockIdx.x & (CL - 1), cid = blockIdx.x >> 4;
    const int isV = rank >> 3, part = rank & 7;
    const int kvrow = part * 32, qrow = rank * 16;
    uint32_t smid;
    asm("mov.u32 %0, %%smid;" : "=r"(smid));
    const int role = (smid & 0xce) == 0;
    const bool leader = elect();
    uint64_t pol;
    asm("createpolicy.fractional.L2::evict_first.b64 %0, 1.0;" : "=l"(pol));
    uint32_t tabv = 0;
    if (warp >= W_PKV) asm volatile("ld.b32 %0, [%1];" : "=r"(tabv) : "l"(&P.tab[2 * role + isV][lane]));

    if (warp == W_PKV) {
        const CUtensorMap* mkv = isV ? &P.mv : &P.mk;
        if (leader) {
#pragma unroll
            for (int k = 0; k < 8; k++) mbar_init(b_kvf + 8 * k, 1);
        }
        __syncwarp();
        cluster_arrive();
        uint32_t tl = tbase + 325 * lane - 835;
        const int rowl = kvrow + (lane & 7) * 256 + head_row(cid, lane >> 3);
#pragma unroll 1
        for (int k = 0; k < 32; k++) {
            if (k == 5) {
                cluster_wait();
                asm volatile("{.reg .b32 x; and.b32 x, %1, 0xffff; add.u32 %0, x, %2;}" : "=r"(tl) : "r"(tabv), "r"(tbase));
            }
            const uint32_t tt = __shfl_sync(0xffffffffu, tl, k);
            const int row = __shfl_sync(0xffffffffu, rowl, k);
            const int s = k & 7;
            if (k >= 8) mbar_wait(b_kve + 8 * s, ((k >> 3) & 1) ^ 1);
            if (leader) mbar_expect_tx(b_kvf + 8 * s, KVB);
            wait_until(tt);
            if (leader) tma_load(s_kv + s * KVB, mkv, row, b_kvf + 8 * s, pol);
        }
        return;
    }
    if (leader) {
        if (warp == W_PQ) {
            mbar_init(b_e, 1);
            asm volatile("fence.mbarrier_init.release.cluster;" ::: "memory");
            mbar_expect_tx(b_e, 4096);
            asm volatile("cp.async.bulk.tensor.3d.shared::cluster.global.mbarrier::complete_tx::bytes [%0], [%1, {%3, %4, %4}], [%2];"
                         :: "r"(s_e), "l"(isV ? &P.mf : &P.me), "r"(b_e), "r"(part * 32), "r"(0) : "memory");
        } else {
            mbar_init(b_kve + 8 * warp, 4);
            mbar_init(b_qe + 8 * warp, 1);
            mbar_init(b_fin + 8 * warp, 1);
            mbar_expect_tx(b_fin + 8 * warp, 2048);
            if (warp >= W_KV) {
                mbar_init(b_in + 8 * (warp - W_KV), 1);
                mbar_expect_tx(b_in + 8 * (warp - W_KV), 4096);
            } else if (warp < 2) {
                mbar_init(b_fr + 8 * warp, 4);
            }
        }
    }
    __syncwarp();
    cluster_arrive();
    cluster_wait();

    if (warp == W_PQ) {
        asm volatile("barrier.sync 1, 160;" ::: "memory");
        uint32_t tl;
        asm volatile("{.reg .b32 x; shr.u32 x, %1, 16; add.u32 %0, x, %2;}" : "=r"(tl) : "r"(tabv), "r"(tbase));
        const int rowl = qrow + (lane & 7) * 256 + head_row(cid, lane >> 3);
#pragma unroll 1
        for (int b = 0; b < 32; b++) {
            const uint32_t tt = __shfl_sync(0xffffffffu, tl, b);
            const int row = __shfl_sync(0xffffffffu, rowl, b);
            const int s = b & 7;
            if (b == 20) {
#pragma unroll
                for (int i = 4; i < 8; i++) mbar_wait(b_qe + 8 * i, 1);
            } else if (b == 24) {
                mbar_wait(b_fin + 16 * 2 + 8 * isV, 0);
                mbar_wait(b_kve + 8 * 3, 1);
            } else if (b >= 8 && b < 20) {
                mbar_wait(b_qe + 8 * s, ((b >> 3) & 1) ^ 1);
            }
            const uint32_t dst = (b >= 24 ? s_kv : s_q) + s * QB;
            wait_until(tt);
            if (leader) tma_load(dst, &P.mq, row, b_qf + 8 * b, pol);
        }
    } else if (warp >= W_KV) {
        const int w = warp - W_KV;
        const uint32_t l7 = lane & 7;
        const uint32_t cA = (w & 1) * 4 + ((lane >> 3) & 1);
        const uint32_t a_base = s_kv + (w >> 1) * 4096 + (l7 + 8 * (lane >> 4)) * 128;
        const uint32_t a0 = a_base + ((cA ^ l7) << 4), a1 = a_base + (((cA + 2) ^ l7) << 4);
        const uint32_t e0 = s_e + l7 * 64 + (((lane >> 3) ^ (l7 >> 1)) << 4);
        const uint32_t dst0 = mapa(s_in + part * 512 + lane * 16, isV * 8 + 2 * w), dst1 = mapa(s_in + part * 512 + lane * 16, isV * 8 + 2 * w + 1);
        const uint32_t rb0 = mapa(b_in, isV * 8 + 2 * w), rb1 = mapa(b_in, isV * 8 + 2 * w + 1);
        const uint32_t vin = s_in + ((lane >> 4) * 16 + (lane & 1) * 8 + ((lane >> 1) & 3)) * 16 + ((lane >> 3) & 1) * 8;
        mbar_wait(b_e, 0);
#pragma unroll 1
        for (int j = 0; j < HPC; j++) {
            float c0[4] = {0, 0, 0, 0}, c1[4] = {0, 0, 0, 0}, c2[4] = {0, 0, 0, 0}, c3[4] = {0, 0, 0, 0};
#pragma unroll 1
            for (int c = 0; c < 8; c++) {
                uint32_t e[4], a[16];
                ldsm4(e0 + c * 512, e);
                if (c == 7 && j > 0) {
                    mbar_wait_cl(b_fin + 16 * (j - 1), 0);
                    mbar_wait_cl(b_fin + 16 * (j - 1) + 8, 0);
                    if (j < 3) mbar_wait(b_fr + 8 * (j - 1), 0);
                }
                mbar_wait(b_kvf + 8 * c, j & 1);
#pragma unroll
                for (int s = 0; s < 2; s++) {
                    ldsm4t(a0 + c * KVB + s * 2048, a + 8 * s);
                    ldsm4t(a1 + c * KVB + s * 2048, a + 8 * s + 4);
                }
#pragma unroll
                for (int s = 0; s < 2; s++) {
                    mma16816(s ? c2 : c0, a + 8 * s, e[2 * s], e[2 * s + 1]);
                    mma16816(s ? c3 : c1, a + 8 * s + 4, e[2 * s], e[2 * s + 1]);
                }
                __syncwarp();
                if (leader) mbar_arrive(b_kve + 8 * c);
            }
            st_async4(dst0, __float_as_uint(c0[0] + c2[0]), __float_as_uint(c0[1] + c2[1]), __float_as_uint(c0[2] + c2[2]),
                      __float_as_uint(c0[3] + c2[3]), rb0 + 8 * j);
            st_async4(dst1, __float_as_uint(c1[0] + c3[0]), __float_as_uint(c1[1] + c3[1]), __float_as_uint(c1[2] + c3[2]),
                      __float_as_uint(c1[3] + c3[3]), rb1 + 8 * j);
            if (w == 3) {
                const uint32_t foff = s_fin + (j & 1) * FINB + rank * 256, fb = b_fin + 16 * j + 8 * isV;
                uint32_t rd[CL], rbar[CL];
#pragma unroll
                for (int r = 0; r < CL; r++) {
                    rd[r] = mapa(foff + lane * 8, r);
                    rbar[r] = mapa(fb, r);
                    asm volatile("" : "+r"(rd[r]), "+r"(rbar[r]));
                }
                mbar_wait_cl(b_in + 8 * j, 0);
                uint32_t w0, w1;
#define F_(v) __uint_as_float(v)
#define S8(A, f) (((F_(A[0].f) + F_(A[1].f)) + (F_(A[2].f) + F_(A[3].f))) + ((F_(A[4].f) + F_(A[5].f)) + (F_(A[6].f) + F_(A[7].f))))
                if (isV) {
                    uint2 x[8], y[8];
#pragma unroll
                    for (int s = 0; s < 8; s++) { x[s] = lds64(vin + s * 512); y[s] = lds64(vin + s * 512 + 64); }
                    w0 = pack_bf16(S8(x, x), S8(x, y));
                    w1 = pack_bf16(S8(y, x), S8(y, y));
                } else {
                    uint4 x[8];
#pragma unroll
                    for (int s = 0; s < 8; s++) x[s] = lds128(s_in + s * 512 + lane * 16);
                    w0 = pack_bf16(S8(x, x), S8(x, y));
                    w1 = pack_bf16(S8(x, z), S8(x, w));
                    asm volatile("movmatrix.sync.aligned.m8n8.trans.b16 %0, %0;" : "+r"(w0));
                    asm volatile("movmatrix.sync.aligned.m8n8.trans.b16 %0, %0;" : "+r"(w1));
                }
#undef S8
#undef F_
#pragma unroll
                for (int r = CL - 1; r >= 0; r--) st_async2(rd[r], w0, w1, rbar[r]);
            }
        }
    } else {
        mbar_wait(b_e, 0);
        if (leader) {
#pragma unroll
            for (int i = 0; i < 8; i++) mbar_init(b_qf + 32 * i + 8 * warp, 1);
#pragma unroll
            for (int i = 0; i < 8; i++) mbar_expect_tx(b_qf + 32 * i + 8 * warp, QB);
            asm volatile("fence.mbarrier_init.release.cluster;" ::: "memory");
        }
        __syncwarp();
        asm volatile("barrier.arrive 1, 160;" ::: "memory");
        const int g = lane >> 2, t = lane & 3;
        const uint32_t qx = lane & 7, qc = lane >> 4, wo = s_q + warp * 4096;
        uint32_t ka = s_fin + lane * 8;
        uint32_t va = s_fin + 2048 + (lane >> 3) * 256 + (lane & 7) * 16;
        uint32_t so0 = wo + 2 * t * 128 + ((g ^ (2 * t)) << 4), so1 = wo + (2 * t + 1) * 128 + ((g ^ (2 * t + 1)) << 4);
        uint32_t qa[4];
#pragma unroll
        for (int u = 0; u < 4; u++) qa[u] = wo + (qx + 8 * ((lane >> 3) & 1)) * 128 + (((2 * u + qc) ^ qx) << 4);
        const int rowl = qrow + warp * 256 + head_row(cid, lane & 3);
#pragma unroll 1
        for (int j = 0; j < HPC; j++) {
            const uint32_t sq = (j == 3 ? s_kv : s_q) + warp * 4096, bq = b_qf + 64 * j + 8 * warp, bf = b_fin + 16 * j;
            const int row = __shfl_sync(0xffffffffu, rowl, j);
            uint32_t vw[16], a[32];
            uint2 kf[8];
            auto load_v = [&] {
#pragma unroll
                for (int x = 0; x < 4; x++) {
                    const uint4 z = lds128(va + (x >> 1) * 1024 + (x & 1) * 128);
                    vw[4 * x] = z.x; vw[4 * x + 1] = z.y; vw[4 * x + 2] = z.z; vw[4 * x + 3] = z.w;
                }
            };
            auto load_q = [&](int h) {
#pragma unroll
                for (int u = 0; u < 8; u++) ldsm4(qa[u & 3] + h * (4 * QB) + (u >> 2) * 2048, a + 4 * u);
            };
            mbar_wait_cl(bf, 0);
#pragma unroll
            for (int u = 0; u < 8; u++) kf[u] = lds64(ka + u * 256);
            mbar_wait(bq, 0);
            const bool late = !mbar_test_cl(bf + 8, 0);
            load_q(0);
            if (!late) { acquire_cl(); load_v(); }
#pragma unroll
            for (int h = 0; h < 2; h++) {
                float sc[4][4];
#pragma unroll
                for (int i = 0; i < 4; i++) { sc[i][0] = sc[i][1] = sc[i][2] = sc[i][3] = 0.f; }
#pragma unroll
                for (int u = 0; u < 4; u++) {
                    mma16816(sc[(2 * u) & 3], a + 8 * u, kf[2 * u].x, kf[2 * u].y);
                    mma16816(sc[(2 * u + 1) & 3], a + 8 * u + 4, kf[2 * u + 1].x, kf[2 * u + 1].y);
                }
                uint32_t p[2];
                softmax8x2((sc[0][0] + sc[1][0]) + (sc[2][0] + sc[3][0]), (sc[0][1] + sc[1][1]) + (sc[2][1] + sc[3][1]),
                           (sc[0][2] + sc[1][2]) + (sc[2][2] + sc[3][2]), (sc[0][3] + sc[1][3]) + (sc[2][3] + sc[3][3]), p[0], p[1]);
                if (h == 0 && late) { mbar_wait_cl(bf + 8, 0); load_v(); }
                __syncwarp();
#pragma unroll
                for (int H = 0; H < 2; H++) {
#pragma unroll
                    for (int u = 0; u < 2; u++) {
                        uint32_t r0[4], r1[4];
#pragma unroll
                        for (int jj = 0; jj < 4; jj++) {
                            float d[4];
                            mma1688z(d, vw[8 * H + 2 * jj], vw[8 * H + 2 * jj + 1], p[u]);
                            r0[jj] = pack_bf16(d[0], d[2]);
                            r1[jj] = pack_bf16(d[1], d[3]);
                        }
                        sts128(so0 + h * (4 * QB) + H * 2048 + u * 1024, r0);
                        sts128(so1 + h * (4 * QB) + H * 2048 + u * 1024, r1);
                    }
                }
                if (h == 1) {
                    const uint32_t dq = j == 2 ? -O_Q : 0;
#pragma unroll
                    for (int u = 0; u < 4; u++) qa[u] += dq;
                    so0 += dq; so1 += dq;
                    const uint32_t df = (j & 1) ? -FINB : FINB;
                    ka += df; va += df;
                }
                asm volatile("fence.proxy.async.shared::cta;" ::: "memory");
                __syncwarp();
                if (leader) asm volatile("cp.async.bulk.tensor.3d.global.shared::cta.bulk_group.L2::cache_hint [%0, {%2, %3, %2}], [%1], %4;"
                                         :: "l"(&P.mo), "r"(sq + h * (4 * QB)), "r"(0), "r"(row + h * 1024), "l"(pol) : "memory");
                if (j < 2) {
                    asm volatile("cp.async.bulk.commit_group;\ncp.async.bulk.wait_group.read 0;" ::: "memory");
                    if (leader) { mbar_arrive(b_qe + 8 * (4 * h + warp)); if (h == 0) mbar_arrive(b_fr + 8 * j); }
                } else if (h == 1 && j == 3) {
                    asm volatile("cp.async.bulk.commit_group;" ::: "memory");
                }
                if (h == 0) { mbar_wait(bq + 32, 0); load_q(1); }
            }
        }
        if (leader) asm volatile("cp.async.bulk.wait_group.read 0;" ::: "memory");
    }
}

typedef CUresult (*EncodeFn)(CUtensorMap*, CUtensorMapDataType, cuuint32_t, void*, const cuuint64_t*, const cuuint64_t*,
                             const cuuint32_t*, const cuuint32_t*, CUtensorMapInterleave, CUtensorMapSwizzle,
                             CUtensorMapL2promotion, CUtensorMapFloatOOBfill);

static void encode3(EncodeFn enc, CUtensorMap* m, const void* p, cuuint64_t d0, cuuint64_t d1, cuuint64_t d2,
                    cuuint64_t s1, cuuint64_t s2, cuuint32_t b1, cuuint32_t b2, cuuint32_t b0 = 64) {
    cuuint64_t dims[3] = {d0, d1, d2}, str[2] = {s1, s2};
    cuuint32_t box[3] = {b0, b1, b2}, es[3] = {1, 1, 1};
    enc(m, CU_TENSOR_MAP_DATA_TYPE_BFLOAT16, 3, (void*)p, dims, str, box, es, CU_TENSOR_MAP_INTERLEAVE_NONE,
        b0 == 64 ? CU_TENSOR_MAP_SWIZZLE_128B : CU_TENSOR_MAP_SWIZZLE_64B, CU_TENSOR_MAP_L2_PROMOTION_NONE, CU_TENSOR_MAP_FLOAT_OOB_FILL_NONE);
}

}

extern "C" void kernel_launch(void* const* d_in, const int* in_sizes, int n_in, void* d_out, int out_size) {
    static lf::EncodeFn enc = nullptr;
    if (!enc) {
        cudaDriverEntryPointQueryResult qr;
        cudaGetDriverEntryPoint("cuTensorMapEncodeTiled", (void**)&enc, cudaEnableDefault, &qr);
        cudaFuncSetAttribute(lf::lf_kernel, cudaFuncAttributeMaxDynamicSharedMemorySize, lf::SMEM);
        cudaFuncSetAttribute(lf::lf_kernel, cudaFuncAttributeNonPortableClusterSizeAllowed, 1);
    }
    lf::Params P;
    lf::encode3(enc, &P.mq, d_in[0], 64, 65536, 2, 256, 128, 16, 2);
    lf::encode3(enc, &P.mk, d_in[1], 64, 65536, 2, 256, 128, 32, 2);
    lf::encode3(enc, &P.mv, d_in[2], 64, 65536, 2, 256, 128, 32, 2);
    lf::encode3(enc, &P.mo, d_out, 64, 65536, 2, 256, 128, 16, 2);
    lf::encode3(enc, &P.me, d_in[3], 256, 8, 8, 4096, 512, 8, 8, 32);
    lf::encode3(enc, &P.mf, d_in[4], 256, 8, 8, 4096, 512, 8, 8, 32);
    for (int r = 0; r < 4; r++)
        for (int i = 0; i < 32; i++) P.tab[r][i] = lf::kTimeKV[r][i] | (uint32_t)lf::kTimeQ[r][i] << 16;
    cudaLaunchConfig_t cfg = {};
    cfg.gridDim = 128; cfg.blockDim = lf::NTHREADS; cfg.dynamicSmemBytes = lf::SMEM; cfg.stream = cudaStreamPerThread;
    cudaLaunchAttribute at[1];
    at[0].id = cudaLaunchAttributeClusterSchedulingPolicyPreference;
    at[0].val.clusterSchedulingPolicyPreference = cudaClusterSchedulingPolicyLoadBalancing;
    cfg.attrs = at; cfg.numAttrs = 1;
    cudaLaunchKernelEx(&cfg, lf::lf_kernel, (const unsigned char*)d_in[1] + lf::HEAD0 * 2048 * 256,
                       (const unsigned char*)d_in[2] + lf::HEAD0 * 2048 * 256, P);
}
```
